```python
import torch

def _softmax(x, axis=-1):
    return torch.softmax(x, dim=axis)
def _gelu(x):
    return torch.nn.functional.gelu(x, approximate="tanh")
def _silu(x):
    return torch.nn.functional.silu(x)
def _sigmoid(x):
    return torch.sigmoid(x)
def _layernorm(x, axis=-1, eps=1e-5):
    m = x.mean(dim=axis, keepdim=True)
    v = x.var(dim=axis, keepdim=True, unbiased=False)
    return (x - m) / torch.sqrt(v + eps)
def _scatter_add(tgt, idx, src, axis=0):
    return tgt.clone().index_add_(axis, idx, src)
def _segment_sum(src, seg, n):
    out = torch.zeros((n,) + src.shape[1:], dtype=src.dtype)
    return out.index_add_(0, seg, src)
def _pad(x, pw):
    flat = tuple(v for pair in reversed(pw) for v in pair)
    return torch.nn.functional.pad(x, flat)

kernel_name = 'sequential_preLN__gqa_block_cached__glu_gated_swiglu__decode'

def setup_inputs():

    _w = (lambda a: (lambda t: t.to(torch.bfloat16) if t.is_floating_point() else t)(torch.as_tensor(a)))
    def _A_setup():
        B, Sq, D = 2, 1, 576
        Hq, Hkv, Sk, Dh = 32, 16, 32768, 128
        assert Hq % Hkv == 0, (Hq, Hkv)
        return {
            "x": _w((lambda *s: torch.randn(*s, dtype=torch.bfloat16) * 0.05)(B, Sq, D)),
            "k_cache": _w((lambda *s: torch.randn(*s, dtype=torch.bfloat16) * 3.2)(B, Hkv, Sk, Dh)),
            "v_cache": _w((lambda *s: torch.randn(*s, dtype=torch.bfloat16) * 1.6)(B, Hkv, Sk, Dh)),
            "wq": _w((lambda *s: torch.randn(*s, dtype=torch.bfloat16) * 3.2)(D, Hq * Dh) * (D ** -0.5)),
            "wo": _w((lambda *s: torch.randn(*s, dtype=torch.bfloat16) * 1.6)(Hq * Dh, D) * ((Hq * Dh) ** -0.5)),
        }
    _A_in = _A_setup()

    def _B_setup():
        B, S, D, F = 2, 1, 576, 4608
        return {
            "x": _w((lambda *s: torch.randn(*s, dtype=torch.bfloat16) * 0.05)(B, S, D)),
            "w1": _w((lambda *s: torch.randn(*s, dtype=torch.bfloat16) * 1.6)(D, F) * (2.0 / D) ** 0.5),
            "w3": _w((lambda *s: torch.randn(*s, dtype=torch.bfloat16) * 1.6)(D, F) * (2.0 / D) ** 0.5),
            "w2": _w((lambda *s: torch.randn(*s, dtype=torch.bfloat16) * 1.6)(F, D) * (2.0 / F) ** 0.5),
        }
    _B_in = _B_setup()

    return {
        "A_x": _A_in["x"],
        "A_k_cache": _A_in["k_cache"],
        "A_v_cache": _A_in["v_cache"],
        "A_wq": _A_in["wq"],
        "A_wo": _A_in["wo"],
        "B_x": _B_in["x"],
        "B_w1": _B_in["w1"],
        "B_w3": _B_in["w3"],
        "B_w2": _B_in["w2"],
    }

def reference(A_x, A_k_cache, A_v_cache, A_wq, A_wo, B_x, B_w1, B_w3, B_w2):
    def _A_ref(x, k_cache, v_cache, wq, wo):
        B, Sq, D = x.shape
        Hq, Dh = 32, 128
        Hkv = k_cache.shape[1]
        rep = Hq // Hkv
        q = (lambda x, *d: x.permute(*d))((x @ wq).reshape(B, Sq, Hq, Dh), 0, 2, 1, 3)
        k = (lambda x, n, axis: torch.repeat_interleave(x, n, dim=axis))(k_cache, rep, axis=1)
        v = (lambda x, n, axis: torch.repeat_interleave(x, n, dim=axis))(v_cache, rep, axis=1)
        scores = torch.einsum("bhqd,bhkd->bhqk", q, k) * (Dh ** -0.5)
        p = _softmax(scores, axis=-1)
        o = torch.einsum("bhqk,bhkd->bhqd", p, v)
        return (lambda x, *d: x.permute(*d))(o, 0, 2, 1, 3).reshape(B, Sq, Hq * Dh) @ wo

    def _B_ref(x, w1, w3, w2):
        gate = torch.einsum("bsd,df->bsf", x, w1)
        up = torch.einsum("bsd,df->bsf", x, w3)
        h = _silu(gate) * up
        out = torch.einsum("bsf,fd->bsd", h, w2)
        return out

    x = A_x
    h = x + _A_ref(_layernorm(x, axis=-1), A_k_cache, A_v_cache, A_wq, A_wo)
    h2 = h + _B_ref(_layernorm(h, axis=-1), B_w1, B_w3, B_w2)
    return h2
```

```cpp
#include <cuda_runtime.h>
#include <cuda_bf16.h>
#include <cuda.h>
#include <stdint.h>

namespace {

constexpr int DM = 576, HKV = 16, SK = 32768, FF = 4608, QD = 4096;
constexpr int NCTA = 128;
constexpr int NTHREADS = 288;
constexpr int TILE = 128;
constexpr int TILE_BYTES = TILE * 256;
constexpr int NIT = SK / 4 / TILE;
constexpr int NSLOT = 6;

constexpr int OFF_BAR = 0;
constexpr int OFF_Q = 128;
constexpr int OFF_ML = 640;
constexpr int OFF_OB = 768;
constexpr int OFF_ACT = 1280;
constexpr int OFF_H = 1536;
constexpr int OFF_RED = 4096;
constexpr int OFF_WO = 12288;
constexpr int WO_BYTES = 128 * 288;
constexpr int OFF_W1 = OFF_WO + WO_BYTES;
constexpr int W13_BOX = 192 * 80;
constexpr int OFF_W3 = OFF_W1 + 3 * W13_BOX;
constexpr int OFF_W2 = OFF_W3 + 3 * W13_BOX;
constexpr int W2_PITCH = 1168;
constexpr int OFF_RING = 35840;
constexpr int SMEM_BYTES = OFF_RING + NSLOT * TILE_BYTES;
static_assert(OFF_W2 + 40 * W2_PITCH <= OFF_RING + 5 * TILE_BYTES, "weights must fit below slot 5");

struct Inbox {
    float a[32][2][4][128];
    float b1[36][32][32];
    float c[36][128][32];
    float ml[32][2][4][2];
    uint32_t h[4][576];
};
constexpr int INBOX_V4 = sizeof(Inbox) / 16;
__device__ __align__(128) Inbox g_in;
__device__ __align__(128) float g_qpart[HKV][8][2][256];
__device__ unsigned g_bar;

#define TS(k)
#define TS_IF(c, k)

constexpr int SPIN_LIMIT = 1 << 22;
constexpr float LOG2E = 1.4426950408889634f;

__device__ __forceinline__ void mbar_init(uint32_t bar, uint32_t cnt) {
    asm volatile("mbarrier.init.shared::cta.b64 [%0], %1;" ::"r"(bar), "r"(cnt) : "memory");
}
__device__ __forceinline__ void mbar_expect(uint32_t bar, uint32_t bytes) {
    asm volatile("mbarrier.arrive.expect_tx.shared::cta.b64 _, [%0], %1;" ::"r"(bar), "r"(bytes) : "memory");
}
__device__ __forceinline__ void mbar_arrive(uint32_t bar) {
    asm volatile("mbarrier.arrive.shared::cta.b64 _, [%0];" ::"r"(bar) : "memory");
}
__device__ __forceinline__ void mbar_wait(uint32_t bar, uint32_t parity) {
    uint32_t ok;
    int it = 0;
    do {
        asm volatile("{.reg .pred p; mbarrier.try_wait.parity.shared::cta.b64 p, [%1], %2; selp.u32 %0, 1, 0, p;}"
                     : "=r"(ok) : "r"(bar), "r"(parity) : "memory");
        if (++it > SPIN_LIMIT) __trap();
    } while (!ok);
}
__device__ __forceinline__ void tma2d(uint32_t dst, const CUtensorMap* tm, int c0, int c1, uint32_t bar, uint64_t pol) {
    asm volatile("cp.async.bulk.tensor.2d.shared::cluster.global.mbarrier::complete_tx::bytes.L2::cache_hint "
                 "[%0], [%1, {%3, %4}], [%2], %5;"
                 ::"r"(dst), "l"(tm), "r"(bar), "r"(c0), "r"(c1), "l"(pol) : "memory");
}
__device__ __forceinline__ void tma2d_nohint(uint32_t dst, const CUtensorMap* tm, int c0, int c1, uint32_t bar) {
    asm volatile("cp.async.bulk.tensor.2d.shared::cluster.global.mbarrier::complete_tx::bytes "
                 "[%0], [%1, {%3, %4}], [%2];"
                 ::"r"(dst), "l"(tm), "r"(bar), "r"(c0), "r"(c1) : "memory");
}
__device__ __forceinline__ void bulk1d(uint32_t dst, const void* src, uint32_t bytes, uint32_t bar, uint64_t pol) {
    asm volatile("cp.async.bulk.shared::cluster.global.mbarrier::complete_tx::bytes.L2::cache_hint "
                 "[%0], [%1], %2, [%3], %4;"
                 ::"r"(dst), "l"(src), "r"(bytes), "r"(bar), "l"(pol) : "memory");
}
__device__ __forceinline__ void bar_sync(int id, int n) { asm volatile("bar.sync %0, %1;" ::"r"(id), "r"(n) : "memory"); }

__device__ __forceinline__ void ldsm4(uint32_t (&r)[4], uint32_t addr) {
    asm volatile("ldmatrix.sync.aligned.m8n8.x4.shared.b16 {%0,%1,%2,%3}, [%4];"
                 : "=r"(r[0]), "=r"(r[1]), "=r"(r[2]), "=r"(r[3]) : "r"(addr) : "memory");
}
__device__ __forceinline__ void ldsm4t(uint32_t (&r)[4], uint32_t addr) {
    asm volatile("ldmatrix.sync.aligned.m8n8.x4.trans.shared.b16 {%0,%1,%2,%3}, [%4];"
                 : "=r"(r[0]), "=r"(r[1]), "=r"(r[2]), "=r"(r[3]) : "r"(addr) : "memory");
}
__device__ __forceinline__ void ldsm2t(uint32_t (&r)[2], uint32_t addr) {
    asm volatile("ldmatrix.sync.aligned.m8n8.x2.trans.shared.b16 {%0,%1}, [%2];"
                 : "=r"(r[0]), "=r"(r[1]) : "r"(addr) : "memory");
}
__device__ __forceinline__ void mma16(float (&c)[4], const uint32_t (&a)[4], uint32_t b0, uint32_t b1) {
    asm volatile("mma.sync.aligned.m16n8k16.row.col.f32.bf16.bf16.f32 {%0,%1,%2,%3}, {%4,%5,%6,%7}, {%8,%9}, {%0,%1,%2,%3};"
                 : "+f"(c[0]), "+f"(c[1]), "+f"(c[2]), "+f"(c[3])
                 : "r"(a[0]), "r"(a[1]), "r"(a[2]), "r"(a[3]), "r"(b0), "r"(b1));
}
__device__ __forceinline__ void mma8(float (&c)[4], const uint32_t (&a)[2], uint32_t b0) {
    asm volatile("mma.sync.aligned.m16n8k8.row.col.f32.bf16.bf16.f32 {%0,%1,%2,%3}, {%4,%5}, {%6}, {%0,%1,%2,%3};"
                 : "+f"(c[0]), "+f"(c[1]), "+f"(c[2]), "+f"(c[3])
                 : "r"(a[0]), "r"(a[1]), "r"(b0));
}
__device__ __forceinline__ uint32_t movm(uint32_t a) {
    uint32_t d;
    asm volatile("movmatrix.sync.aligned.m8n8.trans.b16 %0, %1;" : "=r"(d) : "r"(a));
    return d;
}
__device__ __forceinline__ uint32_t pack_bf16(float lo, float hi) {
    uint32_t d;
    asm("cvt.rn.bf16x2.f32 %0, %1, %2;" : "=r"(d) : "f"(hi), "f"(lo));
    return d;
}
__device__ __forceinline__ float bf_lo(uint32_t w) { return __uint_as_float(w << 16); }
__device__ __forceinline__ float bf_hi(uint32_t w) { return __uint_as_float(w & 0xffff0000u); }
__device__ __forceinline__ float bfr(float x) { return bf_lo(pack_bf16(x, 0.f)); }
__device__ __forceinline__ float ex2(float x) { float y; asm("ex2.approx.ftz.f32 %0, %1;" : "=f"(y) : "f"(x)); return y; }

__device__ __forceinline__ uint32_t nz(float x) { uint32_t u = __float_as_uint(x); return u ? u : 0x80000000u; }
__device__ __forceinline__ void st_rlx(void* p, uint32_t v) { asm volatile("st.relaxed.gpu.global.u32 [%0], %1;" ::"l"(p), "r"(v) : "memory"); }
__device__ __forceinline__ void st_rlx2(void* p, uint32_t a, uint32_t b) {
    asm volatile("st.relaxed.gpu.global.v2.u32 [%0], {%1,%2};" ::"l"(p), "r"(a), "r"(b) : "memory");
}
__device__ __forceinline__ uint32_t ld_rlx(const void* p) {
    uint32_t v;
    asm volatile("ld.relaxed.gpu.global.u32 %0, [%1];" : "=r"(v) : "l"(p) : "memory");
    return v;
}
__device__ __forceinline__ uint4 ld_rlx4(const void* p) {
    uint4 v;
    asm volatile("ld.relaxed.gpu.global.v4.u32 {%0,%1,%2,%3}, [%4];" : "=r"(v.x), "=r"(v.y), "=r"(v.z), "=r"(v.w) : "l"(p) : "memory");
    return v;
}
__device__ __forceinline__ bool all_nz(const uint4& v) { return v.x != 0 && v.y != 0 && v.z != 0 && v.w != 0; }

__device__ __forceinline__ float warp_sum(float v) {
#pragma unroll
    for (int o = 16; o > 0; o >>= 1) v += __shfl_xor_sync(0xffffffffu, v, o);
    return v;
}

__device__ __forceinline__ void ln_stats(const float (&a)[18], const float (&b)[18], float& ma, float& ra, float& mb, float& rb) {
    float sa = 0.f, sb = 0.f;
#pragma unroll
    for (int i = 0; i < 18; i++) { sa += a[i]; sb += b[i]; }
    sa = warp_sum(sa) * (1.f / DM);
    sb = warp_sum(sb) * (1.f / DM);
    float va = 0.f, vb = 0.f;
#pragma unroll
    for (int i = 0; i < 18; i++) { float da = a[i] - sa, db = b[i] - sb; va += da * da; vb += db * db; }
    va = warp_sum(va) * (1.f / DM);
    vb = warp_sum(vb) * (1.f / DM);
    ma = bfr(sa);
    mb = bfr(sb);
    ra = 1.f / bfr(sqrtf(bfr(bfr(va) + 1e-5f)));
    rb = 1.f / bfr(sqrtf(bfr(bfr(vb) + 1e-5f)));
}

__device__ __forceinline__ uint32_t tile_off(int r, int c) {
    int row = 2 * r + (c >> 3);
    return row * 128 + (((c & 7) ^ (row & 7)) << 4);
}

__global__ void __launch_bounds__(NTHREADS, 1)
fused_decode_kernel(const __grid_constant__ CUtensorMap tmK, const __grid_constant__ CUtensorMap tmV,
                    const __grid_constant__ CUtensorMap tmWo, const __grid_constant__ CUtensorMap tmW1,
                    const __grid_constant__ CUtensorMap tmW3,
                    const __nv_bfloat16* __restrict__ x, const __nv_bfloat16* __restrict__ wq,
                    const __nv_bfloat16* __restrict__ w2, __nv_bfloat16* __restrict__ out) {
    extern __shared__ __align__(1024) unsigned char smem[];
    const uint32_t sb = (uint32_t)__cvta_generic_to_shared(smem);
    const int tid = threadIdx.x, warp = tid >> 5, lane = tid & 31;
    const int cta = blockIdx.x;
    const int pair = cta >> 2, split = cta & 3;
    const int bat = pair >> 4, hkv = pair & 15;
    const int g = lane >> 2, t = lane & 3;
    const uint32_t bar_full = sb + OFF_BAR, bar_empty = bar_full + 8 * NSLOT;
    const uint32_t bar_wo = bar_empty + 8 * NSLOT, bar_w13 = bar_wo + 8, bar_w2 = bar_wo + 16;

    const int head = cta >> 2, cq = cta & 3;
    const int ng = 5 - (cta & 1);
    const int f0 = 8 * (9 * (cta >> 1) + 5 * (cta & 1));

    if (warp == 8) {
        uint64_t pol;
        asm volatile("createpolicy.fractional.L2::evict_first.b64 %0, 1.0;" : "=l"(pol));
        const int row0 = 2 * (pair * SK + split * TILE);
        if (lane == 0) {
            TS(0);
            if (sb & 1023) __trap();
#pragma unroll
            for (int s = 0; s < NSLOT; s++) { mbar_init(bar_full + 8 * s, 1); mbar_init(bar_empty + 8 * s, 8); }
            mbar_init(bar_wo, 1); mbar_init(bar_w13, 1); mbar_init(bar_w2, 1);
            asm volatile("fence.mbarrier_init.release.cluster;" ::: "memory");
#pragma unroll
            for (int i = 0; i < NSLOT; i++) {
                mbar_expect(bar_full + 8 * i, TILE_BYTES);
                tma2d(sb + OFF_RING + ((i + 4) % NSLOT) * TILE_BYTES, (i & 1) ? &tmV : &tmK, 0,
                      row0 + (i >> 1) * (8 * TILE), bar_full + 8 * i, pol);
            }
            mbar_expect(bar_wo, WO_BYTES);
            mbar_expect(bar_w13, 6 * W13_BOX);
            mbar_expect(bar_w2, ng * 8 * DM * 2);
        }
        __syncwarp();
        bar_sync(0, NTHREADS);
        if (lane == 0) {
            int l = 0, ph = 0;
            for (int i = NSLOT; i < 2 * NIT; i++) {
                mbar_wait(bar_empty + 8 * l, ph);
                mbar_expect(bar_full + 8 * l, TILE_BYTES);
                int phys = l + 4; if (phys >= NSLOT) phys -= NSLOT;
                tma2d(sb + OFF_RING + phys * TILE_BYTES, (i & 1) ? &tmV : &tmK, 0,
                      row0 + (i >> 1) * (8 * TILE), bar_full + 8 * l, pol);
                if (++l == NSLOT) { l = 0; ph ^= 1; }
                if (i == 2 * NIT - 8) {
                    asm volatile("prefetch.tensormap [%0];" ::"l"(&tmWo) : "memory");
                    asm volatile("prefetch.tensormap [%0];" ::"l"(&tmW1) : "memory");
                    asm volatile("prefetch.tensormap [%0];" ::"l"(&tmW3) : "memory");
                }
            }
            static_assert((2 * NIT) % NSLOT == 2 && ((2 * NIT) / NSLOT) % 2 == 1, "slot schedule");
            mbar_wait(bar_empty + 8 * 2, 0);
            TS(8);
            tma2d(sb + OFF_WO, &tmWo, cq * 144, head * 128, bar_wo, pol);
            tma2d_nohint(sb + OFF_W1, &tmW1, f0, 0, bar_w13);
            mbar_wait(bar_empty + 8 * 3, 0);
            tma2d_nohint(sb + OFF_W1 + W13_BOX, &tmW1, f0, 192, bar_w13);
            tma2d_nohint(sb + OFF_W1 + 2 * W13_BOX, &tmW1, f0, 384, bar_w13);
            mbar_wait(bar_empty + 8 * 4, 0);
            tma2d_nohint(sb + OFF_W3, &tmW3, f0, 0, bar_w13);
            tma2d_nohint(sb + OFF_W3 + W13_BOX, &tmW3, f0, 192, bar_w13);
            mbar_wait(bar_empty + 8 * 5, 0);
            tma2d_nohint(sb + OFF_W3 + 2 * W13_BOX, &tmW3, f0, 384, bar_w13);
        }
        __syncwarp();
        if (lane < 16) bulk1d(sb + OFF_W2 + lane * W2_PITCH, w2 + (size_t)(f0 + lane) * DM, DM * 2, bar_w2, pol);
        if (lane == 0) mbar_wait(bar_empty + 8 * 0, 1);
        __syncwarp();
        if (lane + 16 < ng * 8)
            bulk1d(sb + OFF_W2 + (lane + 16) * W2_PITCH, w2 + (size_t)(f0 + lane + 16) * DM, DM * 2, bar_w2, pol);
    } else {
        const int r = bat * 4 + split;
        const int qrow = 72 * r + 9 * warp;
        uint4 wv[9];
#pragma unroll
        for (int i = 0; i < 9; i++) {
            const void* p = wq + (size_t)(qrow + i) * QD + hkv * 256 + lane * 8;
            asm volatile("ld.global.nc.L1::no_allocate.v4.u32 {%0,%1,%2,%3}, [%4];"
                         : "=r"(wv[i].x), "=r"(wv[i].y), "=r"(wv[i].z), "=r"(wv[i].w) : "l"(p));
        }
        float xa[18], xb[18];
#pragma unroll
        for (int i = 0; i < 9; i++) {
            uint32_t wa = __ldg((const uint32_t*)x + i * 32 + lane);
            uint32_t wb = __ldg((const uint32_t*)x + DM / 2 + i * 32 + lane);
            xa[2 * i] = bf_lo(wa); xa[2 * i + 1] = bf_hi(wa);
            xb[2 * i] = bf_lo(wb); xb[2 * i + 1] = bf_hi(wb);
        }
        float xr = 0.f;
        if (lane < 18) xr = __bfloat162float(x[(lane >= 9 ? DM - 9 : 0) + qrow + lane]);
        {
            uint4* z = (uint4*)&g_in;
            for (int i = cta * 256 + tid; i < INBOX_V4; i += NCTA * 256) z[i] = make_uint4(0, 0, 0, 0);
        }
        bar_sync(0, NTHREADS);
        float ma, ra, mb, rb;
        ln_stats(xa, xb, ma, ra, mb, rb);
        xr = lane >= 9 ? bfr(bfr(xr - mb) * rb) : bfr(bfr(xr - ma) * ra);
        float qa[8], qb[8];
#pragma unroll
        for (int j = 0; j < 8; j++) { qa[j] = 0.f; qb[j] = 0.f; }
#pragma unroll
        for (int i = 0; i < 9; i++) {
            float a = __shfl_sync(0xffffffffu, xr, i), b = __shfl_sync(0xffffffffu, xr, 9 + i);
            uint32_t w[4] = {wv[i].x, wv[i].y, wv[i].z, wv[i].w};
#pragma unroll
            for (int j = 0; j < 4; j++) {
                float lo = bf_lo(w[j]), hi = bf_hi(w[j]);
                qa[2 * j] += a * lo; qa[2 * j + 1] += a * hi;
                qb[2 * j] += b * lo; qb[2 * j + 1] += b * hi;
            }
        }
        TS_IF(tid == 0, 1);
        float* red = (float*)(smem + OFF_RED);
        {
            float4* p = (float4*)(red + warp * 512 + lane * 8);
            p[0] = make_float4(qa[0], qa[1], qa[2], qa[3]);
            p[1] = make_float4(qa[4], qa[5], qa[6], qa[7]);
            p[64] = make_float4(qb[0], qb[1], qb[2], qb[3]);
            p[65] = make_float4(qb[4], qb[5], qb[6], qb[7]);
        }
        bar_sync(1, 256);
        {
            float s0 = 0.f, s1 = 0.f;
#pragma unroll
            for (int w = 0; w < 8; w++) { float2 v = *(float2*)(red + w * 512 + tid * 2); s0 += v.x; s1 += v.y; }
            *(float2*)(&g_qpart[hkv][r][0][0] + tid * 2) = make_float2(s0, s1);
        }
        asm volatile("fence.proxy.async.shared::cta;" ::: "memory");
        bar_sync(1, 256);
        if (tid == 0) {
            __threadfence();
            unsigned ticket = atomicAdd(&g_bar, 1u);
            unsigned target = (ticket & ~(unsigned)(NCTA - 1)) + NCTA;
            int it = 0;
            while ((int)(ld_rlx(&g_bar) - target) < 0) { if (++it > SPIN_LIMIT) __trap(); }
            __threadfence();
        }
        bar_sync(1, 256);
        TS_IF(tid == 0, 2);
        {
            float s = 0.f;
#pragma unroll
            for (int j = 0; j < 8; j++) s += __ldcg(&g_qpart[hkv][j][bat][tid]);
            ((__nv_bfloat16*)(smem + OFF_Q))[tid] = __float2bfloat16(s);
        }
        bar_sync(1, 256);
        uint32_t qf[8][2];
#pragma unroll
        for (int ks = 0; ks < 8; ks++) {
            const uint32_t* qp = (const uint32_t*)(smem + OFF_Q) + (g & 1) * 64 + ks * 8 + t;
            qf[ks][0] = qp[0];
            qf[ks][1] = qp[4];
        }
        TS_IF(tid == 0, 3);

        uint32_t koff[8], voff[8];
#pragma unroll
        for (int j = 0; j < 8; j++) {
            koff[j] = tile_off(warp * 16 + (lane & 7) + ((lane >> 3) & 1) * 8, 2 * j + (lane >> 4));
            voff[j] = tile_off(warp * 16 + (lane & 7) + (lane >> 4) * 8, 2 * j + ((lane >> 3) & 1));
        }
        float o[8][4];
#pragma unroll
        for (int j = 0; j < 8; j++) { o[j][0] = o[j][1] = o[j][2] = o[j][3] = 0.f; }
        float m0 = -3.0e38f, m1 = -3.0e38f, l0 = 0.f, l1 = 0.f;
        int l = 0, ph = 0;
        for (int it = 0; it < NIT; it++) {
            int phys = l + 4; if (phys >= NSLOT) phys -= NSLOT;
            const uint32_t kb = sb + OFF_RING + phys * TILE_BYTES, vb = kb + TILE_BYTES;
            mbar_wait(bar_full + 8 * l, ph);
            float s0[4] = {0.f, 0.f, 0.f, 0.f}, s1[4] = {0.f, 0.f, 0.f, 0.f};
#pragma unroll
            for (int j = 0; j < 8; j += 2) {
                uint32_t a0[4], a1[4];
                ldsm4(a0, kb + koff[j]);
                ldsm4(a1, kb + koff[j + 1]);
                mma16(s0, a0, qf[j][0], qf[j][1]);
                mma16(s1, a1, qf[j + 1][0], qf[j + 1][1]);
            }
            __syncwarp();
            if (lane == 0) mbar_arrive(bar_empty + 8 * l);
            float s[4];
            {
                const float sc = 0.08838834764831845f;
                uint32_t u0 = pack_bf16(s0[0] + s1[0], s0[1] + s1[1]);
                uint32_t u1 = pack_bf16(s0[2] + s1[2], s0[3] + s1[3]);
                u0 = pack_bf16(bf_lo(u0) * sc, bf_hi(u0) * sc);
                u1 = pack_bf16(bf_lo(u1) * sc, bf_hi(u1) * sc);
                s[0] = bf_lo(u0); s[1] = bf_hi(u0); s[2] = bf_lo(u1); s[3] = bf_hi(u1);
            }
            float x0 = fmaxf(s[0], s[2]), x1 = fmaxf(s[1], s[3]);
            if (__any_sync(0xffffffffu, x0 > m0 || x1 > m1)) {
#pragma unroll
                for (int of = 4; of < 32; of <<= 1) {
                    x0 = fmaxf(x0, __shfl_xor_sync(0xffffffffu, x0, of));
                    x1 = fmaxf(x1, __shfl_xor_sync(0xffffffffu, x1, of));
                }
                x0 = fmaxf(x0, m0); x1 = fmaxf(x1, m1);
                float c0 = ex2((m0 - x0) * LOG2E), c1 = ex2((m1 - x1) * LOG2E);
                m0 = x0; m1 = x1;
                l0 *= c0; l1 *= c1;
#pragma unroll
                for (int j = 0; j < 8; j++) { o[j][0] *= c0; o[j][1] *= c1; o[j][2] *= c0; o[j][3] *= c1; }
            }
            float p0 = ex2((s[0] - m0) * LOG2E), p1 = ex2((s[1] - m1) * LOG2E);
            float p2 = ex2((s[2] - m0) * LOG2E), p3 = ex2((s[3] - m1) * LOG2E);
            l0 += p0 + p2; l1 += p1 + p3;
            uint32_t b0 = movm(pack_bf16(p0, p1)), b1 = movm(pack_bf16(p2, p3));
            mbar_wait(bar_full + 8 * (l + 1), ph);
#pragma unroll
            for (int j = 0; j < 8; j++) {
                uint32_t a[4];
                ldsm4t(a, vb + voff[j]);
                mma16(o[j], a, b0, b1);
            }
            __syncwarp();
            if (lane == 0) mbar_arrive(bar_empty + 8 * (l + 1));
            l += 2;
            if (l == NSLOT) { l = 0; ph ^= 1; }
        }
        TS_IF(tid == 0, 4);

#pragma unroll
        for (int of = 4; of < 32; of <<= 1) {
            l0 += __shfl_xor_sync(0xffffffffu, l0, of);
            l1 += __shfl_xor_sync(0xffffffffu, l1, of);
        }
        float* sml = (float*)(smem + OFF_ML);
        if (lane == 0) {
            sml[warp] = m0; sml[8 + warp] = m1; sml[16 + warp] = l0; sml[24 + warp] = l1;
        }
#pragma unroll
        for (int j = 0; j < 8; j++) {
            float v = t == 0 ? o[j][0] : t == 1 ? o[j][1] : t == 2 ? o[j][2] : o[j][3];
            red[warp * 256 + (t & 1) * 128 + j * 16 + (t >> 1) * 8 + g] = v;
        }
        bar_sync(1, 256);
        {
            const int h = tid >> 7;
            float4 ma4 = *(float4*)(sml + h * 8), mb4 = *(float4*)(sml + h * 8 + 4);
            float4 la4 = *(float4*)(sml + 16 + h * 8), lb4 = *(float4*)(sml + 16 + h * 8 + 4);
            float mw[8] = {ma4.x, ma4.y, ma4.z, ma4.w, mb4.x, mb4.y, mb4.z, mb4.w};
            float lw[8] = {la4.x, la4.y, la4.z, la4.w, lb4.x, lb4.y, lb4.z, lb4.w};
            float M = mw[0];
#pragma unroll
            for (int w = 1; w < 8; w++) M = fmaxf(M, mw[w]);
            float acc = 0.f, L = 0.f;
#pragma unroll
            for (int w = 0; w < 8; w++) {
                float e = ex2((mw[w] - M) * LOG2E);
                acc += e * red[w * 256 + tid];
                L += e * lw[w];
            }
            st_rlx(&g_in.a[hkv * 2 + h][bat][split][tid & 127], nz(acc));
            if ((tid & 127) == 0) st_rlx2(&g_in.ml[hkv * 2 + h][bat][split][0], nz(M), nz(L));
        }
        TS_IF(tid == 0, 5);
    }

    uint32_t wof[8][4];
    mbar_wait(bar_wo, 0);
#pragma unroll
    for (int ks = 0; ks < 8; ks++)
        ldsm4t(wof[ks], sb + OFF_WO + (ks * 16 + (lane & 7) + (lane >> 4) * 8) * 288 + (warp * 2 + ((lane >> 3) & 1)) * 16);
    uint32_t xw0 = 0, xw1 = 0;
    if (warp == 8) {
        if (cta < 36) {
            xw0 = __ldg((const uint32_t*)x + cta * 8 + (lane & 7));
            xw1 = __ldg((const uint32_t*)x + DM / 2 + cta * 8 + (lane & 7));
        }
    } else {
        const int b = tid >> 7, d = tid & 127;
        uint32_t v[4];
        uint4 mA, mB;
        int it = 0;
        bool ok;
        do {
#pragma unroll
            for (int s = 0; s < 4; s++) v[s] = ld_rlx(&g_in.a[head][b][s][d]);
            mA = ld_rlx4(&g_in.ml[head][b][0][0]);
            mB = ld_rlx4(&g_in.ml[head][b][2][0]);
            ok = v[0] != 0 && v[1] != 0 && v[2] != 0 && v[3] != 0 && all_nz(mA) && all_nz(mB);
            if (++it > SPIN_LIMIT) __trap();
        } while (!ok);
        float a0 = __uint_as_float(mA.x), a1 = __uint_as_float(mA.z), a2 = __uint_as_float(mB.x), a3 = __uint_as_float(mB.z);
        float M = fmaxf(fmaxf(a0, a1), fmaxf(a2, a3));
        float e0 = ex2((a0 - M) * LOG2E), e1 = ex2((a1 - M) * LOG2E), e2 = ex2((a2 - M) * LOG2E), e3 = ex2((a3 - M) * LOG2E);
        float L = e0 * __uint_as_float(mA.y) + e1 * __uint_as_float(mA.w) + e2 * __uint_as_float(mB.y) + e3 * __uint_as_float(mB.w);
        float acc = e0 * __uint_as_float(v[0]) + e1 * __uint_as_float(v[1]) + e2 * __uint_as_float(v[2]) + e3 * __uint_as_float(v[3]);
        ((__nv_bfloat16*)(smem + OFF_OB))[tid] = __float2bfloat16(__fdividef(acc, L));
    }
    __syncthreads();
    TS_IF(tid == 0, 6);
    {
        float c0[4] = {0.f, 0.f, 0.f, 0.f}, c1[4] = {0.f, 0.f, 0.f, 0.f};
        const uint32_t* op = (const uint32_t*)(smem + OFF_OB) + (g & 1) * 64 + t;
#pragma unroll
        for (int ks = 0; ks < 8; ks += 2) {
            mma16(c0, wof[ks], op[ks * 8], op[ks * 8 + 4]);
            mma16(c1, wof[ks + 1], op[ks * 8 + 8], op[ks * 8 + 12]);
        }
        if (t < 2) {
            float u = t ? c0[2] + c1[2] : c0[0] + c1[0], v = t ? c0[3] + c1[3] : c0[1] + c1[1];
            st_rlx2(&g_in.b1[cq * 9 + warp][head][(t * 8 + g) * 2], nz(u), nz(v));
        }
    }
    if (warp == 8 && cta < 36) {
        uint4 v[8];
        int it = 0;
        bool ok;
        do {
            ok = true;
#pragma unroll
            for (int i = 0; i < 8; i++) v[i] = ld_rlx4(&g_in.b1[cta][i * 4 + (lane >> 3)][(lane & 7) * 4]);
#pragma unroll
            for (int i = 0; i < 8; i++) ok = ok && all_nz(v[i]);
            if (++it > SPIN_LIMIT) __trap();
        } while (!ok);
        float s[4] = {0.f, 0.f, 0.f, 0.f};
#pragma unroll
        for (int i = 0; i < 8; i++) {
            s[0] += __uint_as_float(v[i].x); s[1] += __uint_as_float(v[i].y);
            s[2] += __uint_as_float(v[i].z); s[3] += __uint_as_float(v[i].w);
        }
#pragma unroll
        for (int j = 0; j < 4; j++) {
            s[j] += __shfl_xor_sync(0xffffffffu, s[j], 8);
            s[j] += __shfl_xor_sync(0xffffffffu, s[j], 16);
        }
        uint32_t h0 = pack_bf16(bf_lo(xw0) + bfr(s[0]), bf_lo(xw1) + bfr(s[1]));
        uint32_t h1 = pack_bf16(bf_hi(xw0) + bfr(s[2]), bf_hi(xw1) + bfr(s[3]));
        st_rlx2(&g_in.h[lane >> 3][cta * 16 + (lane & 7) * 2], h0 ? h0 : 0x8000u, h1 ? h1 : 0x8000u);
        TS_IF(lane == 0, 7);
    }
    uint32_t wf[4][5][4];
    mbar_wait(bar_w13, 0);
    TS_IF(tid == 0, 9);
#pragma unroll
    for (int ks = 0; ks < 4; ks++)
#pragma unroll
        for (int gi = 0; gi < 5; gi++)
            ldsm4t(wf[ks][gi], sb + (((lane >> 3) & 1) ? OFF_W3 : OFF_W1) +
                                   (warp * 64 + ks * 16 + (lane & 7) + (lane >> 4) * 8) * 80 + gi * 16);
    uint32_t* hs = (uint32_t*)(smem + OFF_H);
    if (tid < 144) {
        uint4 v;
        int it = 0;
        do {
            v = ld_rlx4(&g_in.h[cta & 3][tid * 4]);
            if (++it > SPIN_LIMIT) __trap();
        } while (!all_nz(v));
        *(uint4*)(hs + tid * 4) = v;
    }
    __syncthreads();
    TS_IF(tid == 0, 10);
    float* red2 = (float*)(smem + OFF_RED);
    {
        float ha[18], hb[18];
#pragma unroll
        for (int i = 0; i < 9; i++) {
            uint2 v = *(const uint2*)(hs + i * 64 + lane * 2);
            ha[2 * i] = bf_lo(v.x); hb[2 * i] = bf_hi(v.x);
            ha[2 * i + 1] = bf_lo(v.y); hb[2 * i + 1] = bf_hi(v.y);
        }
        float ma, ra, mb, rb;
        ln_stats(ha, hb, ma, ra, mb, rb);
        const float mu = (g & 1) ? mb : ma, rs = (g & 1) ? rb : ra;
        float c[5][4];
#pragma unroll
        for (int gi = 0; gi < 5; gi++) { c[gi][0] = c[gi][1] = c[gi][2] = c[gi][3] = 0.f; }
#pragma unroll
        for (int ks = 0; ks < 4; ks++) {
            uint2 u = *(const uint2*)(hs + warp * 64 + ks * 16 + 2 * t);
            uint2 v = *(const uint2*)(hs + warp * 64 + ks * 16 + 2 * t + 8);
            float u0 = (g & 1) ? bf_hi(u.x) : bf_lo(u.x), u1 = (g & 1) ? bf_hi(u.y) : bf_lo(u.y);
            float v0 = (g & 1) ? bf_hi(v.x) : bf_lo(v.x), v1 = (g & 1) ? bf_hi(v.y) : bf_lo(v.y);
            uint32_t b0 = pack_bf16(bfr(u0 - mu) * rs, bfr(u1 - mu) * rs);
            uint32_t b1 = pack_bf16(bfr(v0 - mu) * rs, bfr(v1 - mu) * rs);
#pragma unroll
            for (int gi = 0; gi < 5; gi++) mma16(c[gi], wf[ks][gi], b0, b1);
        }
        if (t < 2) {
#pragma unroll
            for (int gi = 0; gi < 5; gi++)
                *(float2*)(red2 + ((warp * 40 + gi * 8 + g) * 2 + t) * 2) =
                    t ? make_float2(c[gi][1], c[gi][3]) : make_float2(c[gi][0], c[gi][2]);
        }
    }
    __syncthreads();
    if (tid < 80) {
        float gt = 0.f, up = 0.f;
#pragma unroll
        for (int w = 0; w < 9; w++) { float2 v = *(const float2*)(red2 + (w * 80 + tid) * 2); gt += v.x; up += v.y; }
        gt = bfr(gt); up = bfr(up);
        float a = bfr(__fdividef(gt, 1.f + ex2(-gt * LOG2E))) * up;
        ((__nv_bfloat16*)(smem + OFF_ACT))[(tid & 1) * 48 + (tid >> 1)] = __float2bfloat16(a);
    }
    uint32_t w2f[4][2][4], w2g[4][2];
    mbar_wait(bar_w2, 0);
    TS_IF(tid == 0, 11);
#pragma unroll
    for (int i = 0; i < 4; i++) {
        const uint32_t base = sb + OFF_W2 + ((warp * 4 + i) * 2 + ((lane >> 3) & 1)) * 16;
#pragma unroll
        for (int ks = 0; ks < 2; ks++) ldsm4t(w2f[i][ks], base + (ks * 16 + (lane & 7) + (lane >> 4) * 8) * W2_PITCH);
        if (ng == 5) ldsm2t(w2g[i], base + (32 + (lane & 7)) * W2_PITCH);
    }
    __syncthreads();
    {
        const uint32_t* ap = (const uint32_t*)(smem + OFF_ACT) + (g & 1) * 24 + t;
        const uint32_t b00 = ap[0], b01 = ap[4], b10 = ap[8], b11 = ap[12], b2 = ap[16];
#pragma unroll
        for (int i = 0; i < 4; i++) {
            float c[4] = {0.f, 0.f, 0.f, 0.f};
            mma16(c, w2f[i][0], b00, b01);
            mma16(c, w2f[i][1], b10, b11);
            if (ng == 5) mma8(c, w2g[i], b2);
            if (t < 2) st_rlx2(&g_in.c[warp * 4 + i][cta][(t * 8 + g) * 2], nz(t ? c[2] : c[0]), nz(t ? c[3] : c[1]));
        }
    }
    TS_IF(tid == 0, 12);
    if (cta < 36 && warp < 8) {
        uint4 v[4];
        int it = 0;
        bool ok;
        do {
            ok = true;
#pragma unroll
            for (int i = 0; i < 4; i++) v[i] = ld_rlx4(&g_in.c[cta][i * 32 + (tid >> 3)][(lane & 7) * 4]);
#pragma unroll
            for (int i = 0; i < 4; i++) ok = ok && all_nz(v[i]);
            if (++it > SPIN_LIMIT) __trap();
        } while (!ok);
        float s[4] = {0.f, 0.f, 0.f, 0.f};
#pragma unroll
        for (int i = 0; i < 4; i++) {
            s[0] += __uint_as_float(v[i].x); s[1] += __uint_as_float(v[i].y);
            s[2] += __uint_as_float(v[i].z); s[3] += __uint_as_float(v[i].w);
        }
#pragma unroll
        for (int j = 0; j < 4; j++) {
            s[j] += __shfl_xor_sync(0xffffffffu, s[j], 8);
            s[j] += __shfl_xor_sync(0xffffffffu, s[j], 16);
        }
        float* red3 = (float*)(smem + OFF_RED + 6144);
        if (lane < 8) *(float4*)(red3 + warp * 32 + lane * 4) = make_float4(s[0], s[1], s[2], s[3]);
        bar_sync(1, 256);
        if (warp == 0) {
            float acc = 0.f;
#pragma unroll
            for (int w = 0; w < 8; w++) acc += red3[w * 32 + lane];
            const int n = cta * 16 + (lane >> 1), b = lane & 1;
            const uint32_t hw = hs[n];
            out[b * DM + n] = __float2bfloat16((b ? bf_hi(hw) : bf_lo(hw)) + bfr(acc));
            TS_IF(lane == 0, 13);
        }
    }
}

typedef CUresult (*EncodeFn)(CUtensorMap*, CUtensorMapDataType, cuuint32_t, void*, const cuuint64_t*, const cuuint64_t*,
                             const cuuint32_t*, const cuuint32_t*, CUtensorMapInterleave, CUtensorMapSwizzle,
                             CUtensorMapL2promotion, CUtensorMapFloatOOBfill);

void make_map(EncodeFn enc, CUtensorMap* m, const void* p, uint64_t cols, uint64_t rows, uint32_t bc, uint32_t br,
              CUtensorMapSwizzle sw, CUtensorMapL2promotion promo) {
    cuuint64_t dims[2] = {cols, rows};
    cuuint64_t strides[1] = {cols * 2};
    cuuint32_t box[2] = {bc, br};
    cuuint32_t es[2] = {1, 1};
    enc(m, CU_TENSOR_MAP_DATA_TYPE_BFLOAT16, 2, const_cast<void*>(p), dims, strides, box, es,
        CU_TENSOR_MAP_INTERLEAVE_NONE, sw, promo, CU_TENSOR_MAP_FLOAT_OOB_FILL_NONE);
}

}

extern "C" void kernel_launch(void* const* d_in, const int* in_sizes, int n_in, void* d_out, int out_size) {
    static EncodeFn enc = nullptr;
    if (!enc) {
        void* fn = nullptr;
        cudaDriverEntryPointQueryResult qr;
        cudaGetDriverEntryPoint("cuTensorMapEncodeTiled", &fn, cudaEnableDefault, &qr);
        enc = (EncodeFn)fn;
        cudaFuncSetAttribute(fused_decode_kernel, cudaFuncAttributeMaxDynamicSharedMemorySize, SMEM_BYTES);
    }
    CUtensorMap tk, tv, two, tw1, tw3;
    const uint64_t kvrows = (uint64_t)2 * HKV * SK * 2;
    make_map(enc, &tk, d_in[1], 64, kvrows, 64, 2 * TILE, CU_TENSOR_MAP_SWIZZLE_128B, CU_TENSOR_MAP_L2_PROMOTION_L2_128B);
    make_map(enc, &tv, d_in[2], 64, kvrows, 64, 2 * TILE, CU_TENSOR_MAP_SWIZZLE_128B, CU_TENSOR_MAP_L2_PROMOTION_L2_128B);
    make_map(enc, &two, d_in[4], DM, QD, 144, 128, CU_TENSOR_MAP_SWIZZLE_NONE, CU_TENSOR_MAP_L2_PROMOTION_L2_128B);
    make_map(enc, &tw1, d_in[6], FF, DM, 40, 192, CU_TENSOR_MAP_SWIZZLE_NONE, CU_TENSOR_MAP_L2_PROMOTION_L2_128B);
    make_map(enc, &tw3, d_in[7], FF, DM, 40, 192, CU_TENSOR_MAP_SWIZZLE_NONE, CU_TENSOR_MAP_L2_PROMOTION_L2_128B);
    fused_decode_kernel<<<NCTA, NTHREADS, SMEM_BYTES>>>(tk, tv, two, tw1, tw3, (const __nv_bfloat16*)d_in[0],
                                                        (const __nv_bfloat16*)d_in[3], (const __nv_bfloat16*)d_in[8],
                                                        (__nv_bfloat16*)d_out);
}
```

```cpp
#include <cuda_runtime.h>
#include <cuda_bf16.h>
#include <cuda.h>
#include <stdint.h>

namespace {

constexpr int DM = 576, HKV = 16, SK = 32768, FF = 4608, QD = 4096;
constexpr int NCTA = 128;
constexpr int NTHREADS = 320;
constexpr int NEPI = 288;
constexpr int TILE = 128;
constexpr int SUB_BYTES = 64 * 256;
constexpr int NIT = SK / 4 / TILE;
constexpr int NSUB = 4 * NIT;
constexpr int NSLOT = 12;
#define D0 2
#define D1 2
#define XKV 6
#define DRY 1
#define PRE 1

constexpr int OFF_BAR = 0;
constexpr int OFF_TAG = 320;
constexpr int OFF_Q = 384;
constexpr int OFF_ML = 896;
constexpr int OFF_OB = 1024;
constexpr int OFF_ACT = 1536;
constexpr int OFF_ST = 1792;
constexpr int OFF_RED = 4096;
constexpr int OFF_WO = 12288;
constexpr int WO_BYTES = 128 * 288;
constexpr int OFF_W1 = OFF_WO + WO_BYTES;
constexpr int W13_BOX = 192 * 80;
constexpr int OFF_W3 = OFF_W1 + 3 * W13_BOX;
constexpr int OFF_W2 = OFF_W3 + 3 * W13_BOX;
constexpr int W2_PITCH = 1168;
constexpr int OFF_RING = 35840;
constexpr int SMEM_BYTES = OFF_RING + NSLOT * SUB_BYTES;

struct Mail {
    uint32_t q[HKV][8][2][256];
    uint32_t a[32][2][4][128];
    uint32_t ml[32][2][4][8];
    uint32_t b1[36][32][32];
    uint32_t h[4][36][32];
    uint32_t c[36][128][32];
};
__device__ __align__(128) Mail g_mail;
__device__ unsigned g_ticket;

#define TS(k)
#define TS_IF(c, k)

constexpr int SPIN_LIMIT = 1 << 22;
constexpr float LOG2E = 1.4426950408889634f;

__device__ __forceinline__ void mbar_init(uint32_t bar, uint32_t cnt) {
    asm volatile("mbarrier.init.shared::cta.b64 [%0], %1;" ::"r"(bar), "r"(cnt) : "memory");
}
__device__ __forceinline__ void mbar_expect(uint32_t bar, uint32_t bytes) {
    asm volatile("mbarrier.arrive.expect_tx.shared::cta.b64 _, [%0], %1;" ::"r"(bar), "r"(bytes) : "memory");
}
__device__ __forceinline__ void mbar_arrive(uint32_t bar) {
    asm volatile("mbarrier.arrive.shared::cta.b64 _, [%0];" ::"r"(bar) : "memory");
}
__device__ __forceinline__ void mbar_wait(uint32_t bar, uint32_t parity) {
    asm volatile("{\n\t.reg .pred p;\n\t.reg .u32 n;\n\tmov.u32 n, 0;\n"
                 "W: mbarrier.try_wait.parity.shared::cta.b64 p, [%0], %1;\n\t@p bra D;\n\t"
                 "add.u32 n, n, 1;\n\tsetp.lt.u32 p, n, 4194304;\n\t@p bra W;\n\ttrap;\n"
                 "D:\n\t}" ::"r"(bar), "r"(parity) : "memory");
}
__device__ __forceinline__ void tma2d(uint32_t dst, const CUtensorMap* tm, int c0, int c1, uint32_t bar, uint64_t pol) {
    asm volatile("cp.async.bulk.tensor.2d.shared::cluster.global.mbarrier::complete_tx::bytes.L2::cache_hint "
                 "[%0], [%1, {%3, %4}], [%2], %5;"
                 ::"r"(dst), "l"(tm), "r"(bar), "r"(c0), "r"(c1), "l"(pol) : "memory");
}
__device__ __forceinline__ void tma2d_nohint(uint32_t dst, const CUtensorMap* tm, int c0, int c1, uint32_t bar) {
    asm volatile("cp.async.bulk.tensor.2d.shared::cluster.global.mbarrier::complete_tx::bytes "
                 "[%0], [%1, {%3, %4}], [%2];"
                 ::"r"(dst), "l"(tm), "r"(bar), "r"(c0), "r"(c1) : "memory");
}
__device__ __forceinline__ void bulk1d(uint32_t dst, const void* src, uint32_t bytes, uint32_t bar, uint64_t pol) {
    asm volatile("cp.async.bulk.shared::cluster.global.mbarrier::complete_tx::bytes.L2::cache_hint "
                 "[%0], [%1], %2, [%3], %4;"
                 ::"r"(dst), "l"(src), "r"(bytes), "r"(bar), "l"(pol) : "memory");
}
__device__ __forceinline__ void bar_sync(int id, int n) { asm volatile("bar.sync %0, %1;" ::"r"(id), "r"(n) : "memory"); }

__device__ __forceinline__ void ldsm4(uint32_t (&r)[4], uint32_t addr) {
    asm volatile("ldmatrix.sync.aligned.m8n8.x4.shared.b16 {%0,%1,%2,%3}, [%4];"
                 : "=r"(r[0]), "=r"(r[1]), "=r"(r[2]), "=r"(r[3]) : "r"(addr) : "memory");
}
__device__ __forceinline__ void ldsm4t(uint32_t (&r)[4], uint32_t addr) {
    asm volatile("ldmatrix.sync.aligned.m8n8.x4.trans.shared.b16 {%0,%1,%2,%3}, [%4];"
                 : "=r"(r[0]), "=r"(r[1]), "=r"(r[2]), "=r"(r[3]) : "r"(addr) : "memory");
}
__device__ __forceinline__ void ldsm2t(uint32_t (&r)[2], uint32_t addr) {
    asm volatile("ldmatrix.sync.aligned.m8n8.x2.trans.shared.b16 {%0,%1}, [%2];"
                 : "=r"(r[0]), "=r"(r[1]) : "r"(addr) : "memory");
}
__device__ __forceinline__ void mma16(float (&c)[4], const uint32_t (&a)[4], uint32_t b0, uint32_t b1) {
    asm volatile("mma.sync.aligned.m16n8k16.row.col.f32.bf16.bf16.f32 {%0,%1,%2,%3}, {%4,%5,%6,%7}, {%8,%9}, {%0,%1,%2,%3};"
                 : "+f"(c[0]), "+f"(c[1]), "+f"(c[2]), "+f"(c[3])
                 : "r"(a[0]), "r"(a[1]), "r"(a[2]), "r"(a[3]), "r"(b0), "r"(b1));
}
__device__ __forceinline__ void mma8(float (&c)[4], const uint32_t (&a)[2], uint32_t b0) {
    asm volatile("mma.sync.aligned.m16n8k8.row.col.f32.bf16.bf16.f32 {%0,%1,%2,%3}, {%4,%5}, {%6}, {%0,%1,%2,%3};"
                 : "+f"(c[0]), "+f"(c[1]), "+f"(c[2]), "+f"(c[3])
                 : "r"(a[0]), "r"(a[1]), "r"(b0));
}
__device__ __forceinline__ uint32_t movm(uint32_t a) {
    uint32_t d;
    asm volatile("movmatrix.sync.aligned.m8n8.trans.b16 %0, %1;" : "=r"(d) : "r"(a));
    return d;
}
__device__ __forceinline__ uint32_t pack_bf16(float lo, float hi) {
    uint32_t d;
    asm("cvt.rn.bf16x2.f32 %0, %1, %2;" : "=r"(d) : "f"(hi), "f"(lo));
    return d;
}
__device__ __forceinline__ float bf_lo(uint32_t w) { return __uint_as_float(w << 16); }
__device__ __forceinline__ float bf_hi(uint32_t w) { return __uint_as_float(w & 0xffff0000u); }
__device__ __forceinline__ float bfr(float x) { return bf_lo(pack_bf16(x, 0.f)); }
__device__ __forceinline__ float ex2(float x) { float y; asm("ex2.approx.ftz.f32 %0, %1;" : "=f"(y) : "f"(x)); return y; }

__device__ __forceinline__ uint32_t tagged(float x, uint32_t tag) { return (__float_as_uint(x) & ~1u) | tag; }
__device__ __forceinline__ void st_rlx(void* p, uint32_t v, bool go) {
    asm volatile("{.reg .pred p; setp.ne.u32 p, %2, 0; @p st.relaxed.gpu.global.u32 [%0], %1;}" ::"l"(p), "r"(v), "r"((uint32_t)go) : "memory");
}
__device__ __forceinline__ void st_rlx2(void* p, uint32_t a, uint32_t b, bool go) {
    asm volatile("{.reg .pred p; setp.ne.u32 p, %3, 0; @p st.relaxed.gpu.global.v2.u32 [%0], {%1,%2};}"
                 ::"l"(p), "r"(a), "r"(b), "r"((uint32_t)go) : "memory");
}
__device__ __forceinline__ void st_rlx4(void* p, uint32_t a, uint32_t b, uint32_t c, uint32_t d, bool go) {
    asm volatile("{.reg .pred p; setp.ne.u32 p, %5, 0; @p st.relaxed.gpu.global.v4.u32 [%0], {%1,%2,%3,%4};}"
                 ::"l"(p), "r"(a), "r"(b), "r"(c), "r"(d), "r"((uint32_t)go) : "memory");
}
__device__ __forceinline__ void ld_rlx(uint32_t& v, const void* p, bool go) {
    asm volatile("{.reg .pred p; setp.ne.u32 p, %2, 0; @p ld.relaxed.gpu.global.u32 %0, [%1];}" : "+r"(v) : "l"(p), "r"((uint32_t)go) : "memory");
}
__device__ __forceinline__ void ld_rlx2(uint2& v, const void* p, bool go) {
    asm volatile("{.reg .pred p; setp.ne.u32 p, %3, 0; @p ld.relaxed.gpu.global.v2.u32 {%0,%1}, [%2];}"
                 : "+r"(v.x), "+r"(v.y) : "l"(p), "r"((uint32_t)go) : "memory");
}
__device__ __forceinline__ void ld_rlx4(uint4& v, const void* p, bool go) {
    asm volatile("{.reg .pred p; setp.ne.u32 p, %5, 0; @p ld.relaxed.gpu.global.v4.u32 {%0,%1,%2,%3}, [%4];}"
                 : "+r"(v.x), "+r"(v.y), "+r"(v.z), "+r"(v.w) : "l"(p), "r"((uint32_t)go) : "memory");
}
__device__ __forceinline__ void bar_sync_if(int id, int n, bool go) {
    asm volatile("{.reg .pred p; setp.ne.u32 p, %2, 0; @p bar.sync %0, %1;}" ::"r"(id), "r"(n), "r"((uint32_t)go) : "memory");
}
__device__ __forceinline__ void bar_arrive_if(int id, int n, bool go) {
    asm volatile("{.reg .pred p; setp.ne.u32 p, %2, 0; @p bar.arrive %0, %1;}" ::"r"(id), "r"(n), "r"((uint32_t)go) : "memory");
}
__device__ __forceinline__ uint32_t stale(const uint4& v, uint32_t tag) { return ((v.x ^ tag) | (v.y ^ tag)) | ((v.z ^ tag) | (v.w ^ tag)); }
__device__ __forceinline__ float uf(uint32_t u) { return __uint_as_float(u); }

__device__ __forceinline__ float warp_sum(float v) {
#pragma unroll
    for (int o = 16; o > 0; o >>= 1) v += __shfl_xor_sync(0xffffffffu, v, o);
    return v;
}

__device__ __forceinline__ void ln_stats(const float (&a)[18], const float (&b)[18], float& ma, float& ra, float& mb, float& rb) {
    float sa = 0.f, sb = 0.f;
#pragma unroll
    for (int i = 0; i < 18; i++) { sa += a[i]; sb += b[i]; }
    sa = warp_sum(sa) * (1.f / DM);
    sb = warp_sum(sb) * (1.f / DM);
    float va = 0.f, vb = 0.f;
#pragma unroll
    for (int i = 0; i < 18; i++) { float da = a[i] - sa, db = b[i] - sb; va += da * da; vb += db * db; }
    va = warp_sum(va) * (1.f / DM);
    vb = warp_sum(vb) * (1.f / DM);
    ma = bfr(sa);
    mb = bfr(sb);
    ra = 1.f / bfr(sqrtf(bfr(bfr(va) + 1e-5f)));
    rb = 1.f / bfr(sqrtf(bfr(bfr(vb) + 1e-5f)));
}

__device__ __forceinline__ uint32_t tile_off(int r, int c) {
    int row = 2 * r + (c >> 3);
    return row * 128 + (((c & 7) ^ (row & 7)) << 4);
}

__global__ void __launch_bounds__(NTHREADS, 1)
fused_decode_kernel(const __grid_constant__ CUtensorMap tmK, const __grid_constant__ CUtensorMap tmV,
                    const __grid_constant__ CUtensorMap tmWo, const __grid_constant__ CUtensorMap tmW1,
                    const __grid_constant__ CUtensorMap tmW3,
                    const __nv_bfloat16* __restrict__ x, const __nv_bfloat16* __restrict__ wq,
                    const __nv_bfloat16* __restrict__ w2, __nv_bfloat16* __restrict__ out) {
    extern __shared__ __align__(1024) unsigned char smem[];
    const uint32_t sb = (uint32_t)__cvta_generic_to_shared(smem);
    const int tid = threadIdx.x, warp = tid >> 5, lane = tid & 31;
    const int cta = blockIdx.x;
    const int pair = cta >> 2, split = cta & 3;
    const int bat = pair >> 4, hkv = pair & 15;
    const int g = lane >> 2, t = lane & 3;
    const uint32_t bar_full = sb + OFF_BAR, bar_empty = bar_full + 8 * NSLOT;
    const uint32_t bar_w = bar_empty + 8 * NSLOT;

    const int head = cta >> 2, cq = cta & 3;
    const int ng = 5 - (cta & 1);
    const int f0 = 8 * (9 * (cta >> 1) + 5 * (cta & 1));

    if (warp == 9) {
        uint64_t pol;
        asm volatile("createpolicy.fractional.L2::evict_first.b64 %0, 1.0;" : "=l"(pol));
        const int row0 = 2 * (pair * SK + split * TILE);
        auto issue_kv = [&](int i, int l) {
            mbar_expect(bar_full + 8 * l, SUB_BYTES);
            tma2d(sb + OFF_RING + (l < 4 ? l + 8 : l - 4) * SUB_BYTES, (i & 2) ? &tmV : &tmK, 0,
                  row0 + (i >> 2) * (8 * TILE) + (i & 1) * 128, bar_full + 8 * l, pol);
        };
        if (lane == 0) {
            TS(0);
            if (sb & 1023) __trap();
#pragma unroll 1
            for (int s = 0; s < NSLOT; s++) {
                mbar_init(bar_full + 8 * s, 1); mbar_init(bar_empty + 8 * s, 4); mbar_init(bar_w + 8 * s, 1);
            }
            asm volatile("fence.mbarrier_init.release.cluster;" ::: "memory");
#pragma unroll 1
            for (int i = 0; i < D0; i++) issue_kv(i, i);
        }
        __syncwarp();
        asm volatile("bar.arrive 0, %0;" ::"n"(NTHREADS) : "memory");
        if (lane == 0) {
#pragma unroll 1
            for (int i = D0; i < NSLOT; i++) {
                mbar_wait(bar_full + 8 * (i - D0), 0);
                issue_kv(i, i);
            }
            asm volatile("prefetch.tensormap [%0];" ::"l"(&tmWo) : "memory");
            asm volatile("prefetch.tensormap [%0];" ::"l"(&tmW1) : "memory");
            asm volatile("prefetch.tensormap [%0];" ::"l"(&tmW3) : "memory");
            int l = 0, ph = 0;
#pragma unroll 1
            for (int i = NSLOT; i < NSUB - XKV; i++) {
                mbar_wait(bar_empty + 8 * l, ph);
                issue_kv(i, l);
                if (++l == NSLOT) { l = 0; ph ^= 1; }
            }
        }
        __syncwarp();
        static_assert(NSUB % NSLOT == 4, "slot schedule");
        constexpr int NITEM = 11 + XKV;
#pragma unroll 1
        for (int j = 0; j < NITEM; j++) {
            if (j == NITEM - 1 && ng == 4) break;
            const int w = j < 2 ? j : j - XKV;
            const bool kv = j >= 2 && j < 2 + XKV;
            const int i = NSUB - XKV + j - 2;
            {
                const int jp = j - D1;
                const bool pkv = jp < 0 || (jp >= 2 && jp < 2 + XKV);
                const int ip = NSUB - XKV + (jp < 0 ? jp : jp - 2);
                if (pkv) mbar_wait(bar_full + 8 * (ip % NSLOT), (ip / NSLOT) & 1);
                else mbar_wait(bar_w + 8 * (jp < 2 ? jp : jp - XKV), 0);
            }
            {
                const int ic = kv ? i - NSLOT : NSUB - NSLOT + w - 1;
                if (kv || w > 0) mbar_wait(bar_empty + 8 * (ic % NSLOT), (ic / NSLOT) & 1);
            }
            const uint32_t bw = bar_w + 8 * w;
            if (kv) {
                if (lane == 0) issue_kv(i, i % NSLOT);
            } else if (w < 2) {
                if (lane == 0) {
                    mbar_expect(bw, WO_BYTES / 2);
                    tma2d(sb + OFF_WO + w * (WO_BYTES / 2), &tmWo, cq * 144, head * 128 + w * 64, bw, pol);
                }
            } else if (w < 8) {
                if (lane == 0) {
                    mbar_expect(bw, W13_BOX);
                    tma2d_nohint(sb + OFF_W1 + (w - 2) * W13_BOX, w < 5 ? &tmW1 : &tmW3, f0, 192 * (w < 5 ? w - 2 : w - 5), bw);
                }
            } else {
                const int nr = w == 10 ? 8 : 16, r = (w - 8) * 16 + lane;
                if (lane == 0) mbar_expect(bw, nr * DM * 2);
                __syncwarp();
                if (lane < nr) bulk1d(sb + OFF_W2 + r * W2_PITCH, w2 + (size_t)(f0 + r) * DM, DM * 2, bw, pol);
            }
            __syncwarp();
        }
        return;
    }

    float* red = (float*)(smem + OFF_RED);
    float* sml = (float*)(smem + OFF_ML);
    float o[8][4];
#pragma unroll
    for (int j = 0; j < 8; j++) { o[j][0] = o[j][1] = o[j][2] = o[j][3] = 0.f; }
    float xres[4] = {0.f, 0.f, 0.f, 0.f};
    uint32_t tag;
    uint32_t* const a_out = &g_mail.a[hkv * 2 + (t & 1)][bat][split][(warp & 7) * 16 + (t >> 1) * 8 + g];

    if (warp == 8) {
        if (lane == 0) {
            unsigned ticket;
            asm volatile("atom.add.relaxed.gpu.global.u32 %0, [%1], 1;" : "=r"(ticket) : "l"(&g_ticket) : "memory");
            *(volatile uint32_t*)(smem + OFF_TAG) = ((ticket / NCTA) & 1) ^ 1;
        }
        __syncwarp();
        bar_sync(0, NTHREADS);
        tag = *(volatile uint32_t*)(smem + OFF_TAG);
        if (cta < 36) {
            const int n = cta * 16 + (lane & 7);
            xres[0] = __bfloat162float(x[n]); xres[1] = __bfloat162float(x[DM + n]);
            xres[2] = __bfloat162float(x[n + 8]); xres[3] = __bfloat162float(x[DM + n + 8]);
        }
        if (DRY) __nanosleep(12000);
    } else {
        const int r = bat * 4 + split;
        const int qrow = 72 * r + 9 * warp;
        uint4 wv[9];
        {
            const __nv_bfloat16* p = wq + (size_t)qrow * QD + hkv * 256 + lane * 8;
#pragma unroll
            for (int i = 0; i < 9; i++)
                asm volatile("ld.global.nc.L1::no_allocate.v4.u32 {%0,%1,%2,%3}, [%4];"
                             : "=r"(wv[i].x), "=r"(wv[i].y), "=r"(wv[i].z), "=r"(wv[i].w) : "l"(p + i * QD));
        }
        float xa[18], xb[18];
#pragma unroll
        for (int i = 0; i < 9; i++) {
            uint32_t wa = __ldg((const uint32_t*)x + i * 32 + lane);
            uint32_t wb = __ldg((const uint32_t*)x + DM / 2 + i * 32 + lane);
            xa[2 * i] = bf_lo(wa); xa[2 * i + 1] = bf_hi(wa);
            xb[2 * i] = bf_lo(wb); xb[2 * i + 1] = bf_hi(wb);
        }
        float xr = __bfloat162float(x[(lane >= 9 ? DM - 9 : 0) + qrow + min(lane, 17)]);
        bar_sync(0, NTHREADS);
        tag = *(volatile uint32_t*)(smem + OFF_TAG);
        uint32_t* const q_out = &g_mail.q[hkv][r][0][0] + tid * 2;
        st_rlx2(q_out, tag ^ 1, tag ^ 1, PRE);
        float ma, ra, mb, rb;
        ln_stats(xa, xb, ma, ra, mb, rb);
        xr = lane >= 9 ? bfr(bfr(xr - mb) * rb) : bfr(bfr(xr - ma) * ra);
        float qa[8], qb[8];
#pragma unroll
        for (int j = 0; j < 8; j++) { qa[j] = 0.f; qb[j] = 0.f; }
#pragma unroll
        for (int i = 0; i < 9; i++) {
            float a = __shfl_sync(0xffffffffu, xr, i), b = __shfl_sync(0xffffffffu, xr, 9 + i);
            uint32_t w[4] = {wv[i].x, wv[i].y, wv[i].z, wv[i].w};
#pragma unroll
            for (int j = 0; j < 4; j++) {
                float lo = bf_lo(w[j]), hi = bf_hi(w[j]);
                qa[2 * j] += a * lo; qa[2 * j + 1] += a * hi;
                qb[2 * j] += b * lo; qb[2 * j + 1] += b * hi;
            }
        }
        TS_IF(tid == 0, 1);
        {
            float4* p = (float4*)(red + warp * 512 + lane * 8);
            p[0] = make_float4(qa[0], qa[1], qa[2], qa[3]);
            p[1] = make_float4(qa[4], qa[5], qa[6], qa[7]);
            p[64] = make_float4(qb[0], qb[1], qb[2], qb[3]);
            p[65] = make_float4(qb[4], qb[5], qb[6], qb[7]);
        }
        bar_sync(1, 256);
        {
            float s0 = 0.f, s1 = 0.f;
#pragma unroll
            for (int w = 0; w < 8; w++) { float2 v = *(float2*)(red + w * 512 + tid * 2); s0 += v.x; s1 += v.y; }
            st_rlx2(q_out, tagged(s0, tag), tagged(s1, tag), true);
        }
        TS_IF(tid == 0, 2);
        {
            uint32_t v[8], bad;
            int it = 0;
#pragma unroll 1
            do {
                bad = 0;
#pragma unroll
                for (int j = 0; j < 8; j++) { v[j] = 0; ld_rlx(v[j], &g_mail.q[hkv][j][bat][tid], true); }
#pragma unroll
                for (int j = 0; j < 8; j++) bad |= v[j] ^ tag;
                if (++it > SPIN_LIMIT) __trap();
            } while (bad & 1);
            float s = ((uf(v[0]) + uf(v[1])) + (uf(v[2]) + uf(v[3]))) + ((uf(v[4]) + uf(v[5])) + (uf(v[6]) + uf(v[7])));
            ((__nv_bfloat16*)(smem + OFF_Q))[tid] = __float2bfloat16(s);
        }
        asm volatile("fence.proxy.async.shared::cta;" ::: "memory");
        bar_sync(1, 256);
        uint32_t qf[8][2];
#pragma unroll
        for (int ks = 0; ks < 8; ks++) {
            const uint32_t* qp = (const uint32_t*)(smem + OFF_Q) + (g & 1) * 64 + ks * 8 + t;
            qf[ks][0] = qp[0];
            qf[ks][1] = qp[4];
        }
        TS_IF(tid == 0, 3);

        uint32_t koff[8], voff[8];
#pragma unroll
        for (int j = 0; j < 8; j++) {
            koff[j] = tile_off(warp * 16 + (lane & 7) + ((lane >> 3) & 1) * 8, 2 * j + (lane >> 4));
            voff[j] = tile_off(warp * 16 + (lane & 7) + (lane >> 4) * 8, 2 * j + ((lane >> 3) & 1));
        }
        float m0 = -3.0e38f, m1 = -3.0e38f, l0 = 0.f, l1 = 0.f;
        int l = 0, ph = 0;
        const uint32_t bf = bar_full + 8 * (warp >> 2), be = bar_empty + 8 * (warp >> 2);
#pragma unroll 1
        for (int it = 0; it < NIT; it++) {
            const bool last = it == NIT - 1;
            const uint32_t kb = sb + OFF_RING + (l < 4 ? l + 8 : l - 4) * SUB_BYTES, vb = kb + 2 * SUB_BYTES;
            if (PRE && it == NIT - 2) {
                st_rlx(a_out, tag ^ 1, true);
                if (tid < 16) st_rlx(&g_mail.ml[hkv * 2 + (tid >> 3)][bat][split][tid & 7], tag ^ 1, true);
            }
            mbar_wait(bf + 8 * l, ph);
            float s0[4] = {0.f, 0.f, 0.f, 0.f}, s1[4] = {0.f, 0.f, 0.f, 0.f};
#pragma unroll
            for (int j = 0; j < 8; j += 2) {
                uint32_t a0[4], a1[4];
                ldsm4(a0, kb + koff[j]);
                ldsm4(a1, kb + koff[j + 1]);
                mma16(s0, a0, qf[j][0], qf[j][1]);
                mma16(s1, a1, qf[j + 1][0], qf[j + 1][1]);
            }
            __syncwarp();
            if (lane == 0) mbar_arrive(be + 8 * l);
            float s[4];
            {
                const float sc = 0.08838834764831845f;
                uint32_t u0 = pack_bf16(s0[0] + s1[0], s0[1] + s1[1]);
                uint32_t u1 = pack_bf16(s0[2] + s1[2], s0[3] + s1[3]);
                u0 = pack_bf16(bf_lo(u0) * sc, bf_hi(u0) * sc);
                u1 = pack_bf16(bf_lo(u1) * sc, bf_hi(u1) * sc);
                s[0] = bf_lo(u0); s[1] = bf_hi(u0); s[2] = bf_lo(u1); s[3] = bf_hi(u1);
            }
            float x0 = fmaxf(s[0], s[2]), x1 = fmaxf(s[1], s[3]);
            if (__any_sync(0xffffffffu, x0 > m0 || x1 > m1) || last) {
#pragma unroll
                for (int of = 4; of < 32; of <<= 1) {
                    x0 = fmaxf(x0, __shfl_xor_sync(0xffffffffu, x0, of));
                    x1 = fmaxf(x1, __shfl_xor_sync(0xffffffffu, x1, of));
                }
                x0 = fmaxf(x0, m0); x1 = fmaxf(x1, m1);
                if (last) {
                    if (lane == 0) { sml[warp] = x0; sml[8 + warp] = x1; }
                    bar_sync(1, 256);
                    x0 = sml[g]; x1 = sml[8 + g];
#pragma unroll
                    for (int of = 4; of < 32; of <<= 1) {
                        x0 = fmaxf(x0, __shfl_xor_sync(0xffffffffu, x0, of));
                        x1 = fmaxf(x1, __shfl_xor_sync(0xffffffffu, x1, of));
                    }
                }
                float c0 = ex2((m0 - x0) * LOG2E), c1 = ex2((m1 - x1) * LOG2E);
                m0 = x0; m1 = x1;
                l0 *= c0; l1 *= c1;
#pragma unroll
                for (int j = 0; j < 8; j++) { o[j][0] *= c0; o[j][1] *= c1; o[j][2] *= c0; o[j][3] *= c1; }
            }
            float p0 = ex2((s[0] - m0) * LOG2E), p1 = ex2((s[1] - m1) * LOG2E);
            float p2 = ex2((s[2] - m0) * LOG2E), p3 = ex2((s[3] - m1) * LOG2E);
            l0 += p0 + p2; l1 += p1 + p3;
            uint32_t b0 = movm(pack_bf16(p0, p1)), b1 = movm(pack_bf16(p2, p3));
            if (last) {
#pragma unroll
                for (int of = 4; of < 32; of <<= 1) {
                    l0 += __shfl_xor_sync(0xffffffffu, l0, of);
                    l1 += __shfl_xor_sync(0xffffffffu, l1, of);
                }
                if (lane == 0) { sml[16 + warp] = l0; sml[24 + warp] = l1; }
                __syncwarp();
                bar_arrive_if(3, NEPI, true);
            }
            mbar_wait(bf + 8 * (l + 2), ph);
#pragma unroll
            for (int j = 0; j < 8; j++) {
                uint32_t a[4];
                ldsm4t(a, vb + voff[j]);
                mma16(o[j], a, b0, b1);
            }
            __syncwarp();
            if (lane == 0) mbar_arrive(be + 8 * (l + 2));
            l += 4;
            if (l == NSLOT) { l = 0; ph ^= 1; }
        }
        TS_IF(tid == 128, 4);
    }

    int pass = (DRY && warp == 8) ? 0 : 1;
#pragma unroll 1
    for (; pass < 2; pass++) {
        asm volatile("" : "+r"(pass));
        const bool go = pass != 0;
        const int wp = go ? warp : 0, td = go ? tid : lane;
        if (wp < 8) {
            if (t == 0 && go) {
#pragma unroll
                for (int j = 0; j < 8; j++)
                    *(float4*)(red + wp * 256 + j * 32 + g * 4) = make_float4(o[j][0], o[j][1], o[j][2], o[j][3]);
            }
            __syncwarp();
            bar_sync_if(1, 256, go);
            float v[8];
#pragma unroll
            for (int w = 0; w < 8; w++) v[w] = red[w * 256 + td];
            st_rlx(a_out, tagged(((v[0] + v[1]) + (v[2] + v[3])) + ((v[4] + v[5]) + (v[6] + v[7])), tag), go);
            TS_IF(go && tid == 0, 5);
        }
        if (warp == 8) {
            bar_sync_if(3, NEPI, go);
            float m = sml[lane & 15], lsum = sml[16 + (lane & 15)];
#pragma unroll
            for (int of = 1; of < 8; of <<= 1) {
                m = fmaxf(m, __shfl_xor_sync(0xffffffffu, m, of));
                lsum += __shfl_xor_sync(0xffffffffu, lsum, of);
            }
            st_rlx(&g_mail.ml[hkv * 2 + ((lane >> 3) & 1)][bat][split][lane & 7], tagged((lane & 1) ? lsum : m, tag), go && lane < 16);
        }
        const int b = (td >> 7) & 1, d = td & 127;
        float e0, e1, e2, e3;
        {
            uint2 v[4];
#pragma unroll
            for (int s = 0; s < 4; s++) v[s] = make_uint2(tag, tag);
            uint32_t bad;
            int it = 0;
#pragma unroll 1
            do {
#pragma unroll
                for (int s = 0; s < 4; s++) ld_rlx2(v[s], &g_mail.ml[head][b][s][0], go);
                bad = stale(make_uint4(v[0].x, v[0].y, v[1].x, v[1].y), tag) | stale(make_uint4(v[2].x, v[2].y, v[3].x, v[3].y), tag);
                if (++it > SPIN_LIMIT) __trap();
            } while (bad & 1);
            float a0 = uf(v[0].x & ~1u), a1 = uf(v[1].x & ~1u), a2 = uf(v[2].x & ~1u), a3 = uf(v[3].x & ~1u);
            float M = fmaxf(fmaxf(a0, a1), fmaxf(a2, a3));
            e0 = ex2((a0 - M) * LOG2E); e1 = ex2((a1 - M) * LOG2E); e2 = ex2((a2 - M) * LOG2E); e3 = ex2((a3 - M) * LOG2E);
            float L = (e0 * uf(v[0].y) + e1 * uf(v[1].y)) + (e2 * uf(v[2].y) + e3 * uf(v[3].y));
            float rl = __fdividef(1.f, L);
            e0 *= rl; e1 *= rl; e2 *= rl; e3 *= rl;
        }
        uint32_t* const b1_out = &g_mail.b1[cq * 9 + warp][head][g * 4];
        uint32_t* const c_out = &g_mail.c[warp * 4][cta][g * 4];
        uint32_t* const h_out = &g_mail.h[lane >> 3][cta < 36 ? cta : 0][(lane & 7) * 2];
        if (PRE) {
            const uint32_t inv = tag ^ 1;
            st_rlx4(b1_out, inv, inv, inv, inv, go && t == 0);
#pragma unroll
            for (int i = 0; i < 4; i++) st_rlx4(c_out + i * 128 * 32, inv, inv, inv, inv, go && t == 0);
            st_rlx2(h_out, inv, inv, go && warp == 8 && cta < 36);
            st_rlx2(h_out + 16, inv, inv, go && warp == 8 && cta < 36);
        }
        uint32_t wof[8][4];
        if (go) { mbar_wait(bar_w, 0); mbar_wait(bar_w + 8, 0); }
#pragma unroll
        for (int ks = 0; ks < 8; ks++)
            ldsm4t(wof[ks], sb + OFF_WO + (ks * 16 + (lane & 7) + (lane >> 4) * 8) * 288 + (warp * 2 + ((lane >> 3) & 1)) * 16);
        if (wp < 8) {
            uint4 v = make_uint4(tag, tag, tag, tag);
            int it = 0;
#pragma unroll 1
            do {
                ld_rlx(v.x, &g_mail.a[head][b][0][d], go);
                ld_rlx(v.y, &g_mail.a[head][b][1][d], go);
                ld_rlx(v.z, &g_mail.a[head][b][2][d], go);
                ld_rlx(v.w, &g_mail.a[head][b][3][d], go);
                if (++it > SPIN_LIMIT) __trap();
            } while (stale(v, tag) & 1);
            __nv_bfloat16 ob = __float2bfloat16((e0 * uf(v.x) + e1 * uf(v.y)) + (e2 * uf(v.z) + e3 * uf(v.w)));
            if (go) ((__nv_bfloat16*)(smem + OFF_OB))[(d >> 5) * 64 + (b * 4 + ((d & 7) >> 1)) * 8 + ((d >> 3) & 3) * 2 + (d & 1)] = ob;
        }
        __syncwarp();
        bar_sync_if(2, NEPI, go);
        TS_IF(go && tid == 0, 6);
        {
            float c[4][4];
#pragma unroll
            for (int i = 0; i < 4; i++) {
                c[i][0] = c[i][1] = c[i][2] = c[i][3] = 0.f;
                const uint4 ob = *(const uint4*)(smem + OFF_OB + i * 128 + ((g & 1) * 4 + t) * 16);
                mma16(c[i], wof[2 * i], ob.x, ob.y);
                mma16(c[i], wof[2 * i + 1], ob.z, ob.w);
            }
            st_rlx4(b1_out, tagged((c[0][0] + c[1][0]) + (c[2][0] + c[3][0]), tag), tagged((c[0][1] + c[1][1]) + (c[2][1] + c[3][1]), tag),
                    tagged((c[0][2] + c[1][2]) + (c[2][2] + c[3][2]), tag), tagged((c[0][3] + c[1][3]) + (c[2][3] + c[3][3]), tag),
                    go && t == 0);
        }
        TS_IF(go && tid == 0, 8);
        float hres = 0.f;
        if (warp == 8 && cta < 36) {
            uint4 v[8];
#pragma unroll
            for (int i = 0; i < 8; i++) v[i] = make_uint4(tag, tag, tag, tag);
            uint32_t bad;
            int it = 0;
#pragma unroll 1
            do {
                bad = 0;
#pragma unroll
                for (int i = 0; i < 8; i++) ld_rlx4(v[i], &g_mail.b1[cta][i * 4 + (lane >> 3)][(lane & 7) * 4], go);
#pragma unroll
                for (int i = 0; i < 8; i++) bad |= stale(v[i], tag);
                if (++it > SPIN_LIMIT) __trap();
            } while (bad & 1);
            float s[4];
            s[0] = ((uf(v[0].x) + uf(v[1].x)) + (uf(v[2].x) + uf(v[3].x))) + ((uf(v[4].x) + uf(v[5].x)) + (uf(v[6].x) + uf(v[7].x)));
            s[1] = ((uf(v[0].y) + uf(v[1].y)) + (uf(v[2].y) + uf(v[3].y))) + ((uf(v[4].y) + uf(v[5].y)) + (uf(v[6].y) + uf(v[7].y)));
            s[2] = ((uf(v[0].z) + uf(v[1].z)) + (uf(v[2].z) + uf(v[3].z))) + ((uf(v[4].z) + uf(v[5].z)) + (uf(v[6].z) + uf(v[7].z)));
            s[3] = ((uf(v[0].w) + uf(v[1].w)) + (uf(v[2].w) + uf(v[3].w))) + ((uf(v[4].w) + uf(v[5].w)) + (uf(v[6].w) + uf(v[7].w)));
#pragma unroll
            for (int j = 0; j < 4; j++) s[j] += __shfl_xor_sync(0xffffffffu, s[j], 8);
#pragma unroll
            for (int j = 0; j < 4; j++) s[j] += __shfl_xor_sync(0xffffffffu, s[j], 16);
#pragma unroll
            for (int j = 0; j < 4; j++) s[j] = bfr(xres[j] + bfr(s[j]));
            st_rlx2(h_out, __float_as_uint(s[0]) | tag, __float_as_uint(s[2]) | tag, go);
            st_rlx2(h_out + 16, __float_as_uint(s[1]) | tag, __float_as_uint(s[3]) | tag, go);
            TS_IF(go && lane == 0, 7);
#pragma unroll
            for (int j = 0; j < 4; j++) { float u = __shfl_sync(0xffffffffu, s[j], g); if (t == j) hres = u; }
        }
        uint32_t wf[4][5][4];
        if (go) { mbar_wait(bar_w + 8 * (2 + warp / 3), 0); mbar_wait(bar_w + 8 * (5 + warp / 3), 0); }
        TS_IF(go && tid == 0, 9);
#pragma unroll
        for (int ks = 0; ks < 4; ks++)
#pragma unroll
            for (int gi = 0; gi < 5; gi++)
                ldsm4t(wf[ks][gi], sb + (((lane >> 3) & 1) ? OFF_W3 : OFF_W1) +
                                       (warp * 64 + ks * 16 + (lane & 7) + (lane >> 4) * 8) * 80 + gi * 16);
        {
            uint4 v[4];
            const uint32_t one = 0x3f800000u | tag;
#pragma unroll
            for (int ks = 0; ks < 4; ks++) v[ks] = make_uint4(one, one, one, one);
            const uint32_t* hp = &g_mail.h[cta & 3][warp * 4][((g >> 1) & 1) * 16 + t * 4];
            uint32_t bad;
            int it = 0;
#pragma unroll 1
            do {
                bad = 0;
#pragma unroll
                for (int ks = 0; ks < 4; ks++) ld_rlx4(v[ks], hp + ks * 32, go && !(g & 1));
#pragma unroll
                for (int ks = 0; ks < 4; ks++) bad |= stale(v[ks], tag);
                if (++it > SPIN_LIMIT) __trap();
            } while (bad & 1);
            __syncwarp();
            TS_IF(go && tid == 0, 10);
            float c[5][4], gram[4] = {0.f, 0.f, 0.f, 0.f};
#pragma unroll
            for (int gi = 0; gi < 5; gi++) { c[gi][0] = c[gi][1] = c[gi][2] = c[gi][3] = 0.f; }
#pragma unroll
            for (int ks = 0; ks < 4; ks++) {
                const uint32_t b0 = __byte_perm(v[ks].x, v[ks].z, 0x7632), b1 = __byte_perm(v[ks].y, v[ks].w, 0x7632);
#pragma unroll
                for (int gi = 0; gi < 5; gi++) mma16(c[gi], wf[ks][gi], b0, b1);
                const uint32_t ga[4] = {b0, 0u, b1, 0u};
                mma16(gram, ga, b0, b1);
            }
            if (t < 2 && go) {
#pragma unroll
                for (int gi = 0; gi < 5; gi++)
                    *(float4*)(red + ((warp * 40 + gi * 8 + g) * 2 + t) * 4) = make_float4(c[gi][0], c[gi][1], c[gi][2], c[gi][3]);
                if (g == 2 * t) *(float2*)(smem + OFF_ST + (warp * 2 + t) * 8) = make_float2(gram[0], gram[1]);
            }
        }
        __syncwarp();
        bar_sync_if(2, NEPI, go);
        if (td < 80) {
            float4 u[9];
            float2 st[9];
#pragma unroll
            for (int w = 0; w < 9; w++) st[w] = *(const float2*)(smem + OFF_ST + (w * 2 + (td & 1)) * 8);
#pragma unroll
            for (int w = 0; w < 9; w++) u[w] = *(const float4*)(red + (w * 80 + td) * 4);
#define SUM9(a, f) (((a[0].f + a[1].f) + (a[2].f + a[3].f)) + ((a[4].f + a[5].f) + (a[6].f + a[7].f)) + a[8].f)
            const float mean = SUM9(st, y) * (1.f / DM);
            const float var = fmaxf(SUM9(st, x) * (1.f / DM) - mean * mean, 0.f);
            float sd;
            asm("sqrt.approx.f32 %0, %1;" : "=f"(sd) : "f"(bfr(bfr(var) + 1e-5f)));
            const float rs = __fdividef(1.f, bfr(sd)), mu = bfr(mean);
            const float gt = bfr((SUM9(u, x) - mu * SUM9(u, y)) * rs), up = bfr((SUM9(u, z) - mu * SUM9(u, w)) * rs);
            float a = bfr(__fdividef(gt, 1.f + ex2(-gt * LOG2E))) * up;
            if (go) ((__nv_bfloat16*)(smem + OFF_ACT))[(td & 1) * 48 + (td >> 1)] = __float2bfloat16(a);
        }
        __syncwarp();
        TS_IF(go && tid == 0, 11);
        uint32_t w2f[4][2][4], w2g[4][2];
        if (go) { mbar_wait(bar_w + 8 * 8, 0); mbar_wait(bar_w + 8 * 9, 0); if (ng == 5) mbar_wait(bar_w + 8 * 10, 0); }
#pragma unroll
        for (int i = 0; i < 4; i++) {
            const uint32_t base = sb + OFF_W2 + ((warp * 4 + i) * 2 + ((lane >> 3) & 1)) * 16;
#pragma unroll
            for (int ks = 0; ks < 2; ks++) ldsm4t(w2f[i][ks], base + (ks * 16 + (lane & 7) + (lane >> 4) * 8) * W2_PITCH);
            ldsm2t(w2g[i], base + (32 + (lane & 7)) * W2_PITCH);
        }
        bar_sync_if(2, NEPI, go);
        {
            const uint32_t* ap = (const uint32_t*)(smem + OFF_ACT) + (g & 1) * 24 + t;
            const uint32_t b00 = ap[0], b01 = ap[4], b10 = ap[8], b11 = ap[12], b2 = ap[16];
#pragma unroll
            for (int i = 0; i < 4; i++) {
                float c[4] = {0.f, 0.f, 0.f, 0.f};
                mma16(c, w2f[i][0], b00, b01);
                mma16(c, w2f[i][1], b10, b11);
                if (ng == 5) mma8(c, w2g[i], b2);
                st_rlx4(c_out + i * 128 * 32, tagged(c[0], tag), tagged(c[1], tag), tagged(c[2], tag), tagged(c[3], tag), go && t == 0);
            }
        }
        TS_IF(go && tid == 0, 12);
        if (cta < 36) {
            if (wp < 8) {
                uint4 v[4];
#pragma unroll
                for (int i = 0; i < 4; i++) v[i] = make_uint4(tag, tag, tag, tag);
                uint32_t bad;
                int it = 0;
#pragma unroll 1
                do {
                    bad = 0;
#pragma unroll
                    for (int i = 0; i < 4; i++) ld_rlx4(v[i], &g_mail.c[cta][i * 32 + (td >> 3)][(lane & 7) * 4], go);
#pragma unroll
                    for (int i = 0; i < 4; i++) bad |= stale(v[i], tag);
                    if (++it > SPIN_LIMIT) __trap();
                } while (bad & 1);
                float s[4];
                s[0] = (uf(v[0].x) + uf(v[1].x)) + (uf(v[2].x) + uf(v[3].x));
                s[1] = (uf(v[0].y) + uf(v[1].y)) + (uf(v[2].y) + uf(v[3].y));
                s[2] = (uf(v[0].z) + uf(v[1].z)) + (uf(v[2].z) + uf(v[3].z));
                s[3] = (uf(v[0].w) + uf(v[1].w)) + (uf(v[2].w) + uf(v[3].w));
#pragma unroll
                for (int j = 0; j < 4; j++) s[j] += __shfl_xor_sync(0xffffffffu, s[j], 8);
#pragma unroll
                for (int j = 0; j < 4; j++) s[j] += __shfl_xor_sync(0xffffffffu, s[j], 16);
                if (lane < 8 && go) *(float4*)(red + wp * 32 + lane * 4) = make_float4(s[0], s[1], s[2], s[3]);
                __syncwarp();
                bar_arrive_if(3, NEPI, go);
            }
            if (warp == 8) {
                bar_sync_if(3, NEPI, go);
                float v[8];
#pragma unroll
                for (int w = 0; w < 8; w++) v[w] = red[w * 32 + lane];
                const float acc = ((v[0] + v[1]) + (v[2] + v[3])) + ((v[4] + v[5]) + (v[6] + v[7]));
                __nv_bfloat16 res = __float2bfloat16(hres + bfr(acc));
                if (go) out[(t & 1) * DM + cta * 16 + (t >> 1) * 8 + g] = res;
                TS_IF(go && lane == 0, 13);
            }
        }
#pragma unroll
        for (int j = 0; j < 8; j++) { o[j][0] = o[j][1] = o[j][2] = o[j][3] = 0.f; }
    }
}

typedef CUresult (*EncodeFn)(CUtensorMap*, CUtensorMapDataType, cuuint32_t, void*, const cuuint64_t*, const cuuint64_t*,
                             const cuuint32_t*, const cuuint32_t*, CUtensorMapInterleave, CUtensorMapSwizzle,
                             CUtensorMapL2promotion, CUtensorMapFloatOOBfill);

void make_map(EncodeFn enc, CUtensorMap* m, const void* p, uint64_t cols, uint64_t rows, uint32_t bc, uint32_t br,
              CUtensorMapSwizzle sw, CUtensorMapL2promotion promo) {
    cuuint64_t dims[2] = {cols, rows};
    cuuint64_t strides[1] = {cols * 2};
    cuuint32_t box[2] = {bc, br};
    cuuint32_t es[2] = {1, 1};
    enc(m, CU_TENSOR_MAP_DATA_TYPE_BFLOAT16, 2, const_cast<void*>(p), dims, strides, box, es,
        CU_TENSOR_MAP_INTERLEAVE_NONE, sw, promo, CU_TENSOR_MAP_FLOAT_OOB_FILL_NONE);
}

}

extern "C" void kernel_launch(void* const* d_in, const int* in_sizes, int n_in, void* d_out, int out_size) {
    static EncodeFn enc = nullptr;
    if (!enc) {
        void* fn = nullptr;
        cudaDriverEntryPointQueryResult qr;
        cudaGetDriverEntryPoint("cuTensorMapEncodeTiled", &fn, cudaEnableDefault, &qr);
        enc = (EncodeFn)fn;
        cudaFuncSetAttribute(fused_decode_kernel, cudaFuncAttributeMaxDynamicSharedMemorySize, SMEM_BYTES);
    }
    CUtensorMap tk, tv, two, tw1, tw3;
    const uint64_t kvrows = (uint64_t)2 * HKV * SK * 2;
    make_map(enc, &tk, d_in[1], 64, kvrows, 64, 128, CU_TENSOR_MAP_SWIZZLE_128B, CU_TENSOR_MAP_L2_PROMOTION_L2_128B);
    make_map(enc, &tv, d_in[2], 64, kvrows, 64, 128, CU_TENSOR_MAP_SWIZZLE_128B, CU_TENSOR_MAP_L2_PROMOTION_L2_128B);
    make_map(enc, &two, d_in[4], DM, QD, 144, 64, CU_TENSOR_MAP_SWIZZLE_NONE, CU_TENSOR_MAP_L2_PROMOTION_L2_128B);
    make_map(enc, &tw1, d_in[6], FF, DM, 40, 192, CU_TENSOR_MAP_SWIZZLE_NONE, CU_TENSOR_MAP_L2_PROMOTION_L2_128B);
    make_map(enc, &tw3, d_in[7], FF, DM, 40, 192, CU_TENSOR_MAP_SWIZZLE_NONE, CU_TENSOR_MAP_L2_PROMOTION_L2_128B);
    fused_decode_kernel<<<NCTA, NTHREADS, SMEM_BYTES>>>(tk, tv, two, tw1, tw3, (const __nv_bfloat16*)d_in[0],
                                                        (const __nv_bfloat16*)d_in[3], (const __nv_bfloat16*)d_in[8],
                                                        (__nv_bfloat16*)d_out);
}
```

```cpp
#include <cuda_runtime.h>
#include <cuda_bf16.h>
#include <cuda.h>
#include <stdint.h>

namespace {

constexpr int DM = 576, HKV = 16, SK = 32768, FF = 4608, QD = 4096;
constexpr int NCTA = 128;
constexpr int NTHREADS = 320;
constexpr int NEPI = 288;
constexpr int TILE = 128;
constexpr int SUB_BYTES = 64 * 256;
constexpr int NIT = SK / 4 / TILE;
constexpr int NSUB = 4 * NIT;
constexpr int NSLOT = 12;
constexpr int NFFN = 96;
constexpr int NRED = 36;

constexpr int TAU = 640;
constexpr int NTOP = 3;
constexpr int C0 = 500;
constexpr int LEAD = 2260;
constexpr int LEAD1 = 1810, NTAP = 2;
constexpr int RSUB = 4;
constexpr int NFREEZE = 3;
constexpr int P_WO = 740, P_W13 = 565, P_W2 = 570;
static_assert(TAU % NCTA == 0, "");

constexpr int OFF_BAR = 0;
constexpr int OFF_TAG = 320;
constexpr int OFF_OFF = 328;
constexpr int OFF_E = 336;
constexpr int OFF_Q = 384;
constexpr int OFF_ML = 896;
constexpr int OFF_OB = 1024;
constexpr int OFF_ACT = 1536;
constexpr int OFF_ST = 1792;
constexpr int OFF_RED = 2048;
constexpr int OFF_WO = 10240;
constexpr int WO_PITCH = 304;
constexpr int WO_BOX = 64 * WO_PITCH;
constexpr int OFF_W13 = OFF_WO + 2 * WO_BOX;
constexpr int W13_PITCH = 96;
constexpr int W13_BOX = 192 * W13_PITCH;
constexpr int OFF_W2 = OFF_W13 + 6 * W13_BOX;
constexpr int W2_BOX = 48 * 192 * 2;
constexpr int OFF_RING = 35840;
constexpr int SMEM_BYTES = OFF_RING + NSLOT * SUB_BYTES;
static_assert(OFF_W2 % 1024 == 0 && OFF_W2 + 3 * W2_BOX <= OFF_RING + (NSLOT - 1) * SUB_BYTES, "");
static_assert(OFF_W13 + 2 * W13_BOX <= OFF_RING + 4 * SUB_BYTES, "");

struct Mail {
    uint32_t q[HKV][2][2][256];
    uint32_t a[32][2][4][128];
    uint32_t ml[32][2][4][8];
    uint32_t b1[36][32][32];
    uint32_t h[4][36][32];
    uint32_t c[36][NFFN][32];
    unsigned ticket[32];
    unsigned landed[32];
};
__device__ __align__(128) Mail g_mail;

constexpr int SPIN_LIMIT = 1 << 22;
constexpr int CLOCK_LIMIT = 1 << 14;
constexpr float LOG2E = 1.4426950408889634f;

__device__ __forceinline__ void mbar_init(uint32_t bar, uint32_t cnt) {
    asm volatile("mbarrier.init.shared::cta.b64 [%0], %1;" ::"r"(bar), "r"(cnt) : "memory");
}
__device__ __forceinline__ void mbar_expect(uint32_t bar, uint32_t bytes) {
    asm volatile("mbarrier.arrive.expect_tx.shared::cta.b64 _, [%0], %1;" ::"r"(bar), "r"(bytes) : "memory");
}
__device__ __forceinline__ void mbar_arrive(uint32_t bar) {
    asm volatile("mbarrier.arrive.shared::cta.b64 _, [%0];" ::"r"(bar) : "memory");
}
__device__ __forceinline__ void mbar_wait(uint32_t bar, uint32_t parity) {
    asm volatile("{\n\t.reg .pred p;\n\t.reg .u32 n;\n\tmov.u32 n, 0;\n"
                 "W: mbarrier.try_wait.parity.shared::cta.b64 p, [%0], %1;\n\t@p bra D;\n\t"
                 "add.u32 n, n, 1;\n\tsetp.lt.u32 p, n, 1048576;\n\t@p bra W;\n\ttrap;\n"
                 "D:\n\t}" ::"r"(bar), "r"(parity) : "memory");
}
__device__ __forceinline__ bool mbar_test(uint32_t bar, uint32_t parity) {
    uint32_t ok;
    asm volatile("{.reg .pred p; mbarrier.test_wait.parity.shared::cta.b64 p, [%1], %2; selp.u32 %0, 1, 0, p;}"
                 : "=r"(ok) : "r"(bar), "r"(parity) : "memory");
    return ok;
}
__device__ __forceinline__ void tma2d(uint32_t dst, const CUtensorMap* tm, int c0, int c1, uint32_t bar, uint64_t pol) {
    asm volatile("cp.async.bulk.tensor.2d.shared::cluster.global.mbarrier::complete_tx::bytes.L2::cache_hint "
                 "[%0], [%1, {%3, %4}], [%2], %5;"
                 ::"r"(dst), "l"(tm), "r"(bar), "r"(c0), "r"(c1), "l"(pol) : "memory");
}
__device__ __forceinline__ void tma3d(uint32_t dst, const CUtensorMap* tm, int c0, int c1, int c2, uint32_t bar, uint64_t pol) {
    asm volatile("cp.async.bulk.tensor.3d.shared::cluster.global.mbarrier::complete_tx::bytes.L2::cache_hint "
                 "[%0], [%1, {%3, %4, %5}], [%2], %6;"
                 ::"r"(dst), "l"(tm), "r"(bar), "r"(c0), "r"(c1), "r"(c2), "l"(pol) : "memory");
}
__device__ __forceinline__ uint64_t stream_policy() {
    uint64_t pol;
    asm volatile("createpolicy.fractional.L2::evict_first.b64 %0, 1.0;" : "=l"(pol));
    return pol;
}
__device__ __forceinline__ void bar_sync(int id, int n) { asm volatile("barrier.sync %0, %1;" ::"r"(id), "r"(n) : "memory"); }

__device__ __forceinline__ void ldsm4(uint32_t (&r)[4], uint32_t addr) {
    asm volatile("ldmatrix.sync.aligned.m8n8.x4.shared.b16 {%0,%1,%2,%3}, [%4];"
                 : "=r"(r[0]), "=r"(r[1]), "=r"(r[2]), "=r"(r[3]) : "r"(addr) : "memory");
}
__device__ __forceinline__ void ldsm4t(uint32_t (&r)[4], uint32_t addr) {
    asm volatile("ldmatrix.sync.aligned.m8n8.x4.trans.shared.b16 {%0,%1,%2,%3}, [%4];"
                 : "=r"(r[0]), "=r"(r[1]), "=r"(r[2]), "=r"(r[3]) : "r"(addr) : "memory");
}
__device__ __forceinline__ void mma16(float (&c)[4], const uint32_t (&a)[4], uint32_t b0, uint32_t b1) {
    asm volatile("mma.sync.aligned.m16n8k16.row.col.f32.bf16.bf16.f32 {%0,%1,%2,%3}, {%4,%5,%6,%7}, {%8,%9}, {%0,%1,%2,%3};"
                 : "+f"(c[0]), "+f"(c[1]), "+f"(c[2]), "+f"(c[3])
                 : "r"(a[0]), "r"(a[1]), "r"(a[2]), "r"(a[3]), "r"(b0), "r"(b1));
}
__device__ __forceinline__ uint32_t movm(uint32_t a) {
    uint32_t d;
    asm volatile("movmatrix.sync.aligned.m8n8.trans.b16 %0, %1;" : "=r"(d) : "r"(a));
    return d;
}
__device__ __forceinline__ uint32_t pack_bf16(float lo, float hi) {
    uint32_t d;
    asm("cvt.rn.bf16x2.f32 %0, %1, %2;" : "=r"(d) : "f"(hi), "f"(lo));
    return d;
}
__device__ __forceinline__ float bf_lo(uint32_t w) { return __uint_as_float(w << 16); }
__device__ __forceinline__ float bf_hi(uint32_t w) { return __uint_as_float(w & 0xffff0000u); }
__device__ __forceinline__ float bfr(float x) { return bf_lo(pack_bf16(x, 0.f)); }
__device__ __forceinline__ float ex2(float x) { float y; asm("ex2.approx.ftz.f32 %0, %1;" : "=f"(y) : "f"(x)); return y; }

__device__ __forceinline__ uint32_t tagged(float x, uint32_t tag) {
    uint32_t r;
    asm("lop3.b32 %0, %1, 0xfffffffe, %2, 0xea;" : "=r"(r) : "r"(__float_as_uint(x)), "r"(tag));
    return r;
}
__device__ __forceinline__ void st_rlx(void* p, uint32_t v) {
    asm volatile("st.relaxed.gpu.global.u32 [%0], %1;" ::"l"(p), "r"(v) : "memory");
}
__device__ __forceinline__ void st_rlx4(void* p, uint32_t a, uint32_t b, uint32_t c, uint32_t d) {
    asm volatile("st.relaxed.gpu.global.v4.u32 [%0], {%1,%2,%3,%4};" ::"l"(p), "r"(a), "r"(b), "r"(c), "r"(d) : "memory");
}
__device__ __forceinline__ void st_rlx4_if(bool go, void* p, uint32_t a, uint32_t b, uint32_t c, uint32_t d) {
    asm volatile("{.reg .pred p; setp.ne.u32 p, %5, 0; @p st.relaxed.gpu.global.v4.u32 [%0], {%1,%2,%3,%4};}"
                 ::"l"(p), "r"(a), "r"(b), "r"(c), "r"(d), "r"((uint32_t)go) : "memory");
}
__device__ __forceinline__ uint32_t ld_rlx(const void* p) {
    uint32_t v;
    asm volatile("ld.relaxed.gpu.global.u32 %0, [%1];" : "=r"(v) : "l"(p) : "memory");
    return v;
}
__device__ __forceinline__ uint2 ld_rlx2(const void* p) {
    uint2 v;
    asm volatile("ld.relaxed.gpu.global.v2.u32 {%0,%1}, [%2];" : "=r"(v.x), "=r"(v.y) : "l"(p) : "memory");
    return v;
}
__device__ __forceinline__ uint4 ld_rlx4(const void* p) {
    uint4 v;
    asm volatile("ld.relaxed.gpu.global.v4.u32 {%0,%1,%2,%3}, [%4];" : "=r"(v.x), "=r"(v.y), "=r"(v.z), "=r"(v.w) : "l"(p) : "memory");
    return v;
}
__device__ __forceinline__ void bar_arrive(int id, int n) { asm volatile("barrier.arrive %0, %1;" ::"r"(id), "r"(n) : "memory"); }
__device__ __forceinline__ uint32_t stale2(uint32_t a, uint32_t b, uint32_t tag) {
    uint32_t r;
    asm("lop3.b32 %0, %1, %2, %3, 0x7e;" : "=r"(r) : "r"(a), "r"(b), "r"(tag));
    return r;
}
__device__ __forceinline__ uint32_t or3(uint32_t a, uint32_t b, uint32_t c) {
    uint32_t r;
    asm("lop3.b32 %0, %1, %2, %3, 0xfe;" : "=r"(r) : "r"(a), "r"(b), "r"(c));
    return r;
}
__device__ __forceinline__ uint32_t stale4(uint32_t acc, const uint4& v, uint32_t tag) {
    return or3(acc, stale2(v.x, v.y, tag), stale2(v.z, v.w, tag));
}
__device__ __forceinline__ void refresh(uint32_t& v, const void* p, uint32_t tag) {
    asm volatile("{.reg .pred p; .reg .b32 r; lop3.b32 r, %0, %2, 1, 0x28; setp.ne.u32 p, r, 0; @p ld.relaxed.gpu.global.u32 %0, [%1];}"
                 : "+r"(v) : "l"(p), "r"(tag) : "memory");
}
__device__ __forceinline__ bool retry(uint32_t bad, int& it) {
    if (++it > SPIN_LIMIT) __trap();
    return __any_sync(0xffffffffu, bad & 1);
}
__device__ __forceinline__ float uf(uint32_t u) { return __uint_as_float(u & ~1u); }
__device__ __forceinline__ uint32_t now_ns() {
    uint32_t t;
    asm volatile("mov.u32 %0, %globaltimer_lo;" : "=r"(t) :: "memory");
    return t;
}

__device__ __forceinline__ float warp_sum(float v) {
#pragma unroll
    for (int o = 16; o > 0; o >>= 1) v += __shfl_xor_sync(0xffffffffu, v, o);
    return v;
}

__device__ __forceinline__ void ln_stats(const float (&a)[18], const float (&b)[18], float& ma, float& ra, float& mb, float& rb) {
    float sa = 0.f, sb = 0.f;
#pragma unroll
    for (int i = 0; i < 18; i++) { sa += a[i]; sb += b[i]; }
    sa = warp_sum(sa) * (1.f / DM);
    sb = warp_sum(sb) * (1.f / DM);
    float va = 0.f, vb = 0.f;
#pragma unroll
    for (int i = 0; i < 18; i++) { float da = a[i] - sa, db = b[i] - sb; va += da * da; vb += db * db; }
    va = warp_sum(va) * (1.f / DM);
    vb = warp_sum(vb) * (1.f / DM);
    ma = bfr(sa);
    mb = bfr(sb);
    ra = 1.f / bfr(sqrtf(bfr(bfr(va) + 1e-5f)));
    rb = 1.f / bfr(sqrtf(bfr(bfr(vb) + 1e-5f)));
}

__device__ __forceinline__ uint32_t tile_off(int r, int c) {
    const int row = 2 * r + (c >> 3);
    return row * 128 + (((c & 7) ^ (row & 7)) << 4);
}

__global__ void __launch_bounds__(NTHREADS, 1)
fused_decode_kernel(const __nv_bfloat16* wq, const __nv_bfloat16* x, Mail* mail,
                    __nv_bfloat16* out,
                    const __grid_constant__ CUtensorMap tmK, const __grid_constant__ CUtensorMap tmV,
                    const __grid_constant__ CUtensorMap tmWo, const __grid_constant__ CUtensorMap tmW1,
                    const __grid_constant__ CUtensorMap tmW3, const __grid_constant__ CUtensorMap tmW2) {
    extern __shared__ __align__(1024) unsigned char smem[];
    const uint32_t sb = (uint32_t)__cvta_generic_to_shared(smem);
    const int tid = threadIdx.x, lane = tid & 31;
    const int cta = blockIdx.x;
    const int pair = cta >> 2, split = cta & 3;
    const int bat = pair >> 4, hkv = pair & 15;
    uint4 wv[9];
    {
        const uint64_t pol = stream_policy();
        const __nv_bfloat16* p = wq + (size_t)(288 * bat + 36 * (tid >> 5) + (lane >> 3)) * QD + (cta & 63) * 64 + (lane & 7) * 8;
#pragma unroll
        for (int i = 0; i < 9; i++)
            asm volatile("{.reg .pred p; setp.lt.u32 p, %5, 256; @p ld.relaxed.gpu.global.L2::cache_hint.v4.u32 {%0,%1,%2,%3}, [%4], %6;}"
                         : "=r"(wv[i].x), "=r"(wv[i].y), "=r"(wv[i].z), "=r"(wv[i].w)
                         : "l"(p + i * 4 * QD), "r"(tid), "l"(pol) : "memory");
    }
    const uint32_t tstart = now_ns();
    const int row0 = 2 * (pair * SK + split * TILE);
    if (tid == 288) {
        const uint64_t pol = stream_policy();
#pragma unroll
        for (int i = 0; i < NTOP; i++) mbar_init(sb + OFF_BAR + 8 * i, 1);
        asm volatile("fence.mbarrier_init.release.cluster;" ::: "memory");
#pragma unroll
        for (int i = 0; i < NTOP; i++) {
            mbar_expect(sb + OFF_BAR + 8 * i, SUB_BYTES);
            tma2d(sb + OFF_RING + (i + 8) * SUB_BYTES, (i & 2) ? &tmV : &tmK, 0, row0 + (i & 1) * 128, sb + OFF_BAR + 8 * i, pol);
        }
    }
    const int warp = __shfl_sync(0xffffffffu, tid >> 5, 0);
    const int g = lane >> 2, t = lane & 3;
    const uint32_t bar_full = sb + OFF_BAR, bar_empty = bar_full + 8 * NSLOT;
    const uint32_t bar_w = bar_empty + 8 * NSLOT;

    const int head = cta >> 2, cq = cta & 3;
    const int fc = cta - (NCTA - NFFN);

    if (warp == 9) {
        const uint64_t pol = stream_policy();
        auto issue_kv = [&](int i, int l) {
            mbar_expect(bar_full + 8 * l, SUB_BYTES);
            tma2d(sb + OFF_RING + (l < 4 ? l + 8 : l - 4) * SUB_BYTES, (i & 2) ? &tmV : &tmK, 0,
                  row0 + (i >> 2) * (8 * TILE) + (i & 1) * 128, bar_full + 8 * l, pol);
        };
        if (lane < NSLOT) {
            if (lane >= NTOP) mbar_init(bar_full + 8 * lane, 1);
            mbar_init(bar_empty + 8 * lane, 4);
            if (lane < 7) mbar_init(bar_w + 8 * lane, lane < 4 ? 2 : 1);
            *(volatile uint32_t*)(smem + OFF_OFF) = tstart + C0 + LEAD;
            asm volatile("fence.mbarrier_init.release.cluster;" ::: "memory");
        }
        __syncwarp();
        bar_arrive(7, NTHREADS);
        if (sb & 1023) __trap();
        const uint32_t stagger = cta * (TAU / NCTA);
        int l = NTOP, ph = 1;
#pragma unroll 1
        for (int i = NTOP; i < NSUB; i++) {
            if (i == NSUB - 16 && lane == 0) {
                asm volatile("prefetch.tensormap [%0];" ::"l"(&tmWo) : "memory");
                asm volatile("prefetch.tensormap [%0];" ::"l"(&tmW1) : "memory");
                asm volatile("prefetch.tensormap [%0];" ::"l"(&tmW3) : "memory");
                asm volatile("prefetch.tensormap [%0];" ::"l"(&tmW2) : "memory");
            }
            mbar_wait(bar_empty + 8 * l, ph);
            const uint32_t rel = stagger + i * TAU - (i < NSUB - NTAP ? LEAD : LEAD1);
            for (int it = 0; (int)(now_ns() - rel - *(volatile uint32_t*)(smem + OFF_OFF)) < 0 && it < CLOCK_LIMIT; it++) {}
            if (lane == 0) issue_kv(i, l);
            __syncwarp();
            if (++l == NSLOT) { l = 0; ph ^= 1; }
        }
        static_assert(NSUB % NSLOT == 4 && (NSUB / NSLOT) % 2 == 1, "slot schedule");
        uint32_t due = *(volatile uint32_t*)(smem + OFF_OFF) + stagger + NSUB * TAU - LEAD1;
        {
            const int w = lane;
            const CUtensorMap* tm = w < 2 ? &tmWo : w >= 8 ? &tmW2 : (w & 1) ? &tmW3 : &tmW1;
            const int dst = w < 2 ? OFF_WO + w * WO_BOX : w < 8 ? OFF_W13 + (w - 2) * W13_BOX : OFF_W2 + (w - 8) * W2_BOX;
            const int bytes = w < 2 ? WO_BOX : w < 8 ? W13_BOX : W2_BOX;
            const int c0 = w >= 2 && w < 8 ? 48 * fc : 0;
            const int c1 = w < 2 ? cq : w < 8 ? 0 : 3 * (10 - w);
            const int c2 = w < 2 ? head * 128 + w * 64 : w < 8 ? 96 * (w & ~1) - 192 : 48 * fc;
            const uint32_t bw = bar_w + 8 * (w < 8 ? w >> 1 : w - 4);
            due += w < 2 ? w * P_WO : w < 8 ? 2 * P_WO + (w - 2) * P_W13 : 2 * P_WO + 6 * P_W13 + (w - 8) * P_W2;
#pragma unroll 1
            for (int k = 0; k < (fc >= 0 ? 11 : 2); k++) {
                if (k == 1 || k == 4) {
                    if (lane < (k == 1 ? 4 : NSLOT - 1)) mbar_wait(bar_empty + 8 * (lane < 8 ? lane + 4 : lane - 8), lane < 8 ? 0 : 1);
                    __syncwarp();
                }
                if (k < 4 || k == 5 || k == 7) {
                    mbar_wait(k < 4 ? bar_full + 8 * k : bar_w + 8 * ((k >> 1) - 2), k < 4 ? 1 : 0);
                    due += max(0, (int)(now_ns() - __shfl_sync(0xffffffffu, due, k)));
                }
                if (lane == k) {
                    mbar_expect(bw, bytes);
                    for (int it = 0; (int)(now_ns() - due) < 0 && it < CLOCK_LIMIT; it++) {}
                    tma3d(sb + dst, tm, c0, c1, c2, bw, pol);
                }
                __syncwarp();
            }
        }
        return;
    }

    float* red = (float*)(smem + OFF_RED);
    float* sml = (float*)(smem + OFF_ML);
    float xres = 0.f;
    uint32_t tag;
    uint32_t* const h_out = &mail->h[0][cta < NRED ? cta : 0][(t & 1) * 16 + g * 2 + (t >> 1)];

    if (warp == 8) {
        if (lane == 0) {
            unsigned ticket;
            asm volatile("atom.add.relaxed.gpu.global.u32 %0, [%1], 1;" : "=r"(ticket) : "l"(mail->ticket) : "memory");
            *(volatile uint32_t*)(smem + OFF_TAG) = ticket / NCTA;
        }
        __syncwarp();
        tag = (*(volatile uint32_t*)(smem + OFF_TAG) & 1) ^ 1;
        const uint32_t inv = tag ^ 1;
        st_rlx4(&mail->q[hkv][lane >> 4][bat][split * 64 + (lane & 15) * 4], inv, inv, inv, inv);
        bar_sync(7, NTHREADS);
        if (lane == 0) {
            const uint32_t base = *(volatile uint32_t*)(smem + OFF_TAG) * (NCTA * NSUB);
            int it = 0;
            uint32_t n;
            __nanosleep(10000);
#pragma unroll 1
            do {
                __nanosleep(100);
                n = ld_rlx(mail->landed) - base;
                if (n >= 16 * NCTA) *(volatile uint32_t*)(smem + OFF_OFF) = now_ns() - n * (TAU / NCTA);
                if (++it > SPIN_LIMIT) __trap();
            } while (n < (NSUB - NFREEZE) * NCTA);
        }
        __syncwarp();
        bar_sync(3, NEPI);
        {
            float m = sml[lane & 15], lsum = sml[16 + (lane & 15)];
#pragma unroll
            for (int of = 1; of < 8; of <<= 1) {
                m = fmaxf(m, __shfl_xor_sync(0xffffffffu, m, of));
                lsum += __shfl_xor_sync(0xffffffffu, lsum, of);
            }
            if (lane < 16) st_rlx(&mail->ml[hkv * 2 + (lane >> 3)][bat][split][lane & 7], tagged((lane & 1) ? lsum : m, tag));
        }
        if (cta < NRED) xres = __bfloat162float(x[(t & 1) * DM + cta * 16 + (t >> 1) * 8 + g]);
        {
#pragma unroll
            for (int i = 0; i < 3; i++)
                if (i < 2 || lane < 8) st_rlx4(&mail->b1[cq * 9 + i * 4 + (lane >> 3)][head][(lane & 7) * 4], inv, inv, inv, inv);
            if (cta < NRED) st_rlx4(&mail->h[lane >> 3][cta][(lane & 7) * 4], inv, inv, inv, inv);
            if (fc >= 0) {
#pragma unroll
                for (int i = 0; i < 9; i++) st_rlx4(&mail->c[i * 4 + (lane >> 3)][fc][(lane & 7) * 4], inv, inv, inv, inv);
            }
        }
        uint2 v;
        int it = 0;
#pragma unroll 1
        do { v = ld_rlx2(&mail->ml[head][(lane >> 2) & 1][lane & 3][0]); } while (retry(stale2(v.x, v.y, tag), it));
        const float m = uf(v.x);
        float M = fmaxf(m, __shfl_xor_sync(0xffffffffu, m, 1));
        M = fmaxf(M, __shfl_xor_sync(0xffffffffu, M, 2));
        const float e = ex2((m - M) * LOG2E);
        float L = e * uf(v.y);
        L += __shfl_xor_sync(0xffffffffu, L, 1);
        L += __shfl_xor_sync(0xffffffffu, L, 2);
        if (lane < 8) ((float*)(smem + OFF_E))[lane] = __fdividef(e, L);
        __syncwarp();
        bar_arrive(4, NEPI);
    } else {
        const int qrow = 288 * bat + 36 * warp;
        float xa[18], xb[18];
#pragma unroll
        for (int i = 0; i < 9; i++) {
            uint32_t wa = ((const uint32_t*)x)[i * 32 + lane];
            uint32_t wb = ((const uint32_t*)x)[DM / 2 + i * 32 + lane];
            xa[2 * i] = bf_lo(wa); xa[2 * i + 1] = bf_hi(wa);
            xb[2 * i] = bf_lo(wb); xb[2 * i + 1] = bf_hi(wb);
        }
        float xr0 = __bfloat162float(x[qrow + lane]), xr1 = __bfloat162float(x[DM + qrow + lane]);
        float xr2 = __bfloat162float(x[((lane >> 2) & 1) * DM + qrow + 32 + t]);
        uint32_t* const q_out = &mail->q[hkv][tid >> 7][bat][split * 64 + ((tid >> 1) & 63)];
        float ma, ra, mb, rb;
        ln_stats(xa, xb, ma, ra, mb, rb);
        xr0 = bfr(bfr(xr0 - ma) * ra);
        xr1 = bfr(bfr(xr1 - mb) * rb);
        xr2 = (lane & 4) ? bfr(bfr(xr2 - mb) * rb) : bfr(bfr(xr2 - ma) * ra);
        float qa[8], qb[8];
#pragma unroll
        for (int j = 0; j < 8; j++) { qa[j] = 0.f; qb[j] = 0.f; }
#pragma unroll
        for (int i = 0; i < 9; i++) {
            const float a = i < 8 ? __shfl_sync(0xffffffffu, xr0, 4 * i + (lane >> 3)) : __shfl_sync(0xffffffffu, xr2, lane >> 3);
            const float b = i < 8 ? __shfl_sync(0xffffffffu, xr1, 4 * i + (lane >> 3)) : __shfl_sync(0xffffffffu, xr2, 4 + (lane >> 3));
            uint32_t w[4] = {wv[i].x, wv[i].y, wv[i].z, wv[i].w};
#pragma unroll
            for (int j = 0; j < 4; j++) {
                float lo = bf_lo(w[j]), hi = bf_hi(w[j]);
                qa[2 * j] += a * lo; qa[2 * j + 1] += a * hi;
                qb[2 * j] += b * lo; qb[2 * j + 1] += b * hi;
            }
        }
        {
            float4* p = (float4*)(red + (tid >> 3) * 128 + (lane & 7) * 8);
            p[0] = make_float4(qa[0], qa[1], qa[2], qa[3]);
            p[1] = make_float4(qa[4], qa[5], qa[6], qa[7]);
            p[16] = make_float4(qb[0], qb[1], qb[2], qb[3]);
            p[17] = make_float4(qb[4], qb[5], qb[6], qb[7]);
        }
        bar_sync(7, NTHREADS);
        tag = (*(volatile uint32_t*)(smem + OFF_TAG) & 1) ^ 1;
        {
            float s0 = 0.f, s1 = 0.f;
#pragma unroll
            for (int i = 0; i < 16; i += 2) {
                s0 += red[((tid & 1) * 16 + i) * 128 + (tid >> 1)];
                s1 += red[((tid & 1) * 16 + i + 1) * 128 + (tid >> 1)];
            }
            s0 += s1;
            s0 += __shfl_xor_sync(0xffffffffu, s0, 1);
            if (!(tid & 1)) st_rlx(q_out, tagged(s0, tag));
        }
        {
            uint32_t v0 = tag ^ 1, v1 = tag ^ 1;
            int it = 0;
#pragma unroll 1
            do {
                refresh(v0, &mail->q[hkv][bat][0][tid], tag);
                refresh(v1, &mail->q[hkv][bat][1][tid], tag);
            } while (retry(stale2(v0, v1, tag), it));
            ((__nv_bfloat16*)(smem + OFF_Q))[tid] = __float2bfloat16(uf(v0) + uf(v1));
        }
        asm volatile("fence.proxy.async.shared::cta;" ::: "memory");
        bar_sync(1, 256);
        uint32_t qf[8][2];
#pragma unroll
        for (int ks = 0; ks < 8; ks++) {
            const uint32_t* qp = (const uint32_t*)(smem + OFF_Q) + (g & 1) * 64 + ks * 8 + t;
            qf[ks][0] = qp[0];
            qf[ks][1] = qp[4];
        }

        uint32_t koff[8], voff[8];
#pragma unroll
        for (int j = 0; j < 8; j++) {
            koff[j] = tile_off(warp * 16 + (lane & 7) + ((lane >> 3) & 1) * 8, 2 * j + (lane >> 4));
            voff[j] = tile_off(warp * 16 + (lane & 7) + (lane >> 4) * 8, 2 * j + ((lane >> 3) & 1));
        }
        uint32_t* const a_out = &mail->a[hkv * 2 + (t & 1)][bat][split][warp * 16 + (t >> 1) * 8 + g];
        float o[8][4];
#pragma unroll
        for (int j = 0; j < 8; j++) { o[j][0] = o[j][1] = o[j][2] = o[j][3] = 0.f; }
        float m0 = -3.0e38f, m1 = -3.0e38f, l0 = 0.f, l1 = 0.f;
        const bool count = (tid & 127) == 0 && cta % RSUB == 0;
        int l = 0, ph = 0;
        const uint32_t bf = bar_full + 8 * (warp >> 2), be = bar_empty + 8 * (warp >> 2);
#pragma unroll 1
        for (int it = 0; it < NIT; it++) {
            const bool last = it == NIT - 1;
            const uint32_t kb = sb + OFF_RING + (l < 4 ? l + 8 : l - 4) * SUB_BYTES, vb = kb + 2 * SUB_BYTES;
            if (it == NIT - 2) {
                st_rlx(a_out, tag ^ 1);
                if (tid < 16) st_rlx(&mail->ml[hkv * 2 + (tid >> 3)][bat][split][tid & 7], tag ^ 1);
            }
            mbar_wait(bf + 8 * l, ph);
            if (count) asm volatile("red.relaxed.gpu.global.add.u32 [%0], %1;" ::"l"(mail->landed), "n"(RSUB) : "memory");
            float s0[4] = {0.f, 0.f, 0.f, 0.f}, s1[4] = {0.f, 0.f, 0.f, 0.f};
#pragma unroll
            for (int j = 0; j < 4; j++) {
                uint32_t a0[4], a1[4];
                ldsm4(a0, kb + koff[j]);
                ldsm4(a1, kb + koff[j + 4]);
                mma16(s0, a0, qf[j][0], qf[j][1]);
                mma16(s1, a1, qf[j + 4][0], qf[j + 4][1]);
            }
            __syncwarp();
            if (lane == 0) mbar_arrive(be + 8 * l);
            float s[4];
            {
                const float sc = 0.08838834764831845f;
                uint32_t u0 = pack_bf16(s0[0] + s1[0], s0[1] + s1[1]);
                uint32_t u1 = pack_bf16(s0[2] + s1[2], s0[3] + s1[3]);
                u0 = pack_bf16(bf_lo(u0) * sc, bf_hi(u0) * sc);
                u1 = pack_bf16(bf_lo(u1) * sc, bf_hi(u1) * sc);
                s[0] = bf_lo(u0); s[1] = bf_hi(u0); s[2] = bf_lo(u1); s[3] = bf_hi(u1);
            }
            float x0 = fmaxf(s[0], s[2]), x1 = fmaxf(s[1], s[3]);
            if (__any_sync(0xffffffffu, x0 > m0 || x1 > m1) || last) {
#pragma unroll
                for (int of = 4; of < 32; of <<= 1) {
                    x0 = fmaxf(x0, __shfl_xor_sync(0xffffffffu, x0, of));
                    x1 = fmaxf(x1, __shfl_xor_sync(0xffffffffu, x1, of));
                }
                x0 = fmaxf(x0, m0); x1 = fmaxf(x1, m1);
                if (last) {
                    if (lane == 0) { sml[warp] = x0; sml[8 + warp] = x1; }
                    bar_sync(1, 256);
                    x0 = sml[g]; x1 = sml[8 + g];
#pragma unroll
                    for (int of = 4; of < 32; of <<= 1) {
                        x0 = fmaxf(x0, __shfl_xor_sync(0xffffffffu, x0, of));
                        x1 = fmaxf(x1, __shfl_xor_sync(0xffffffffu, x1, of));
                    }
                }
                float c0 = ex2((m0 - x0) * LOG2E), c1 = ex2((m1 - x1) * LOG2E);
                m0 = x0; m1 = x1;
                l0 *= c0; l1 *= c1;
#pragma unroll
                for (int j = 0; j < 8; j++) { o[j][0] *= c0; o[j][1] *= c1; o[j][2] *= c0; o[j][3] *= c1; }
            }
            float p0 = ex2((s[0] - m0) * LOG2E), p1 = ex2((s[1] - m1) * LOG2E);
            float p2 = ex2((s[2] - m0) * LOG2E), p3 = ex2((s[3] - m1) * LOG2E);
            l0 += p0 + p2; l1 += p1 + p3;
            uint32_t b0 = movm(pack_bf16(p0, p1)), b1 = movm(pack_bf16(p2, p3));
            if (last) {
#pragma unroll
                for (int of = 4; of < 32; of <<= 1) {
                    l0 += __shfl_xor_sync(0xffffffffu, l0, of);
                    l1 += __shfl_xor_sync(0xffffffffu, l1, of);
                }
                if (lane == 0) { sml[16 + warp] = l0; sml[24 + warp] = l1; }
                __syncwarp();
                bar_arrive(3, NEPI);
            }
            mbar_wait(bf + 8 * (l + 2), ph);
            if (count) asm volatile("red.relaxed.gpu.global.add.u32 [%0], %1;" ::"l"(mail->landed), "n"(RSUB) : "memory");
#pragma unroll
            for (int j = 0; j < 8; j++) {
                uint32_t a[4];
                ldsm4t(a, vb + voff[j]);
                mma16(o[j], a, b0, b1);
            }
            __syncwarp();
            if (lane == 0) mbar_arrive(be + 8 * (l + 2));
            l += 4;
            if (l == NSLOT) { l = 0; ph ^= 1; }
        }
        if (t == 0) {
#pragma unroll
            for (int j = 0; j < 8; j++)
                *(float4*)(red + warp * 256 + j * 32 + g * 4) = make_float4(o[j][0], o[j][1], o[j][2], o[j][3]);
        }
        __syncwarp();
        bar_sync(1, 256);
        float v[8];
#pragma unroll
        for (int w = 0; w < 8; w++) v[w] = red[w * 256 + tid];
        st_rlx(a_out, tagged(((v[0] + v[1]) + (v[2] + v[3])) + ((v[4] + v[5]) + (v[6] + v[7])), tag));
        bar_sync(4, NEPI);
    }

    {
        uint32_t wof[8][4];
        const int b = (tid >> 7) & 1, d = tid & 127;
        const uint32_t* ap = &mail->a[head][b][0][d];
        uint4 v = make_uint4(tag, tag, tag, tag);
        if (warp < 8) { v.x = ld_rlx(ap); v.y = ld_rlx(ap + 128); v.z = ld_rlx(ap + 256); v.w = ld_rlx(ap + 384); }
        const uint32_t wob = sb + OFF_WO + ((lane & 7) + (lane >> 4) * 8) * WO_PITCH + (warp * 2 + ((lane >> 3) & 1)) * 16;
        const bool early = __all_sync(0xffffffffu, mbar_test(bar_w, 0));
        if (early) {
#pragma unroll
            for (int ks = 0; ks < 8; ks++) ldsm4t(wof[ks], wob + ks * 16 * WO_PITCH);
        }
        if (warp < 8) {
            const float4 e = *(const float4*)(smem + OFF_E + b * 16);
            __nv_bfloat16* obp = (__nv_bfloat16*)(smem + OFF_OB) + (d >> 5) * 64 + (b * 4 + ((d & 7) >> 1)) * 8 + ((d >> 3) & 3) * 2 + (d & 1);
            int it = 0;
#pragma unroll 1
            while (retry(stale4(0, v, tag), it)) {
                v.x = ld_rlx(ap); v.y = ld_rlx(ap + 128); v.z = ld_rlx(ap + 256); v.w = ld_rlx(ap + 384);
            }
            *obp = __float2bfloat16((e.x * uf(v.x) + e.y * uf(v.y)) + (e.z * uf(v.z) + e.w * uf(v.w)));
        }
        if (!early) {
            mbar_wait(bar_w, 0);
#pragma unroll
            for (int ks = 0; ks < 8; ks++) ldsm4t(wof[ks], wob + ks * 16 * WO_PITCH);
        }
        uint32_t* const b1_out = &mail->b1[cq * 9 + warp][head][g * 4];
        bar_sync(2, NEPI);
        float c[4][4];
#pragma unroll
        for (int i = 0; i < 4; i++) {
            c[i][0] = c[i][1] = c[i][2] = c[i][3] = 0.f;
            const uint4 ob = *(const uint4*)(smem + OFF_OB + i * 128 + ((g & 1) * 4 + t) * 16);
            mma16(c[i], wof[2 * i], ob.x, ob.y);
            mma16(c[i], wof[2 * i + 1], ob.z, ob.w);
        }
        if (t == 0)
            st_rlx4(b1_out, tagged((c[0][0] + c[1][0]) + (c[2][0] + c[3][0]), tag), tagged((c[0][1] + c[1][1]) + (c[2][1] + c[3][1]), tag),
                    tagged((c[0][2] + c[1][2]) + (c[2][2] + c[3][2]), tag), tagged((c[0][3] + c[1][3]) + (c[2][3] + c[3][3]), tag));
        __syncwarp();
    }
    float hres = 0.f;
    if (cta < NRED) {
        float* red2 = (float*)(smem + OFF_RED + 14336);
        if (warp < 8) {
            const uint32_t* bp = &mail->b1[cta][tid >> 3][(lane & 7) * 4];
            uint4 v;
            int it = 0;
#pragma unroll 1
            do { v = ld_rlx4(bp); } while (retry(stale4(0, v, tag), it));
            float s[4] = {uf(v.x), uf(v.y), uf(v.z), uf(v.w)};
#pragma unroll
            for (int j = 0; j < 4; j++) s[j] += __shfl_xor_sync(0xffffffffu, s[j], 8);
#pragma unroll
            for (int j = 0; j < 4; j++) s[j] += __shfl_xor_sync(0xffffffffu, s[j], 16);
            if (lane < 8) *(float4*)(red2 + warp * 32 + lane * 4) = make_float4(s[0], s[1], s[2], s[3]);
            __syncwarp();
            bar_arrive(6, NEPI);
        } else {
            bar_sync(6, NEPI);
            float v[8];
#pragma unroll
            for (int w = 0; w < 8; w++) v[w] = red2[w * 32 + lane];
            hres = bfr(xres + bfr(((v[0] + v[1]) + (v[2] + v[3])) + ((v[4] + v[5]) + (v[6] + v[7]))));
#pragma unroll
            for (int i = 0; i < 4; i++) st_rlx(h_out + i * 36 * 32, __float_as_uint(hres) | tag);
        }
    }
    if (fc >= 0) {
        {
            uint32_t wf[4][6][4], hb[4][2];
            float gr0, gr1;
            const int box = warp / 3;
            const uint32_t base = sb + OFF_W13 + (box + ((lane >> 3) & 1)) * W13_BOX + (warp * 64 + (lane & 7) + (lane >> 4) * 8) * W13_PITCH;
            const uint32_t* hp = &mail->h[cta & 3][warp * 4][((g >> 1) & 1) * 16 + t * 4];
#pragma unroll 1
            for (int step = 0; step < 2; step++) {
                if ((step == 0) == (box < 2)) {
                    mbar_wait(bar_w + 8 * (1 + box), 0);
#pragma unroll
                    for (int ks = 0; ks < 4; ks++)
#pragma unroll
                        for (int gi = 0; gi < 6; gi++) ldsm4t(wf[ks][gi], base + ks * 16 * W13_PITCH + gi * 16);
                } else {
                    uint4 v[4];
                    uint32_t bad;
                    int it = 0;
#pragma unroll 1
                    do {
#pragma unroll
                        for (int ks = 0; ks < 4; ks++) v[ks] = ld_rlx4(hp + ks * 32);
                        bad = 0;
#pragma unroll
                        for (int ks = 0; ks < 4; ks++) bad = stale4(bad, v[ks], tag);
                    } while (retry(bad, it));
#pragma unroll
                    for (int ks = 0; ks < 4; ks++) {
                        hb[ks][0] = (g & 1) ? 0x3f803f80u : __byte_perm(v[ks].x, v[ks].z, 0x7632);
                        hb[ks][1] = (g & 1) ? 0x3f803f80u : __byte_perm(v[ks].y, v[ks].w, 0x7632);
                    }
                    float gram[4] = {0.f, 0.f, 0.f, 0.f};
#pragma unroll
                    for (int ks = 0; ks < 4; ks++) {
                        const uint32_t ga[4] = {hb[ks][0], 0u, hb[ks][1], 0u};
                        mma16(gram, ga, hb[ks][0], hb[ks][1]);
                    }
                    gr0 = gram[0]; gr1 = gram[1];
                }
            }
            float c[6][4];
#pragma unroll
            for (int gi = 0; gi < 6; gi++) { c[gi][0] = c[gi][1] = c[gi][2] = c[gi][3] = 0.f; }
#pragma unroll
            for (int ks = 0; ks < 4; ks++)
#pragma unroll
                for (int gi = 0; gi < 6; gi++) mma16(c[gi], wf[ks][gi], hb[ks][0], hb[ks][1]);
            if (t < 2) {
                if (g == 2 * t) *(float2*)(smem + OFF_ST + (warp * 2 + t) * 8) = make_float2(gr0, gr1);
#pragma unroll
                for (int gi = 0; gi < 6; gi++)
                    *(float4*)(red + ((warp * 48 + gi * 8 + g) * 2 + t) * 4) = make_float4(c[gi][0], c[gi][1], c[gi][2], c[gi][3]);
            }
            __syncwarp();
        }
        if (warp < 3) {
            bar_sync(2, NEPI);
            float4 u[9];
            float2 st[9];
#pragma unroll
            for (int w = 0; w < 9; w++) st[w] = *(const float2*)(smem + OFF_ST + (w * 2 + (tid & 1)) * 8);
#pragma unroll
            for (int w = 0; w < 9; w++) u[w] = *(const float4*)(red + (w * 96 + tid) * 4);
#define SUM9(a, f) (((a[0].f + a[1].f) + (a[2].f + a[3].f)) + ((a[4].f + a[5].f) + (a[6].f + a[7].f)) + a[8].f)
            const float mean = SUM9(st, y) * (1.f / DM);
            const float var = fmaxf(SUM9(st, x) * (1.f / DM) - mean * mean, 0.f);
            float sd, rs, rg;
            asm("sqrt.approx.ftz.f32 %0, %1;" : "=f"(sd) : "f"(bfr(bfr(var) + 1e-5f)));
            asm("rcp.approx.ftz.f32 %0, %1;" : "=f"(rs) : "f"(bfr(sd)));
            const float mu = bfr(mean);
            const float gt = bfr((SUM9(u, x) - mu * SUM9(u, y)) * rs), up = bfr((SUM9(u, z) - mu * SUM9(u, w)) * rs);
            asm("rcp.approx.ftz.f32 %0, %1;" : "=f"(rg) : "f"(1.f + ex2(-gt * LOG2E)));
            ((__nv_bfloat16*)(smem + OFF_ACT))[(tid & 1) * 48 + (tid >> 1)] = __float2bfloat16(bfr(gt * rg) * up);
            __syncwarp();
            bar_arrive(5, NEPI);
        } else {
            bar_arrive(2, NEPI);
            uint32_t w2f[3][2][3][4], w2a[2];
#pragma unroll
            for (int i = 0; i < 2; i++) {
                const int cc = ((warp - 3) * 2 + i) * 2 + ((lane >> 3) & 1), u = ((lane & 7) + (lane >> 4) * 8) * 3 + (cc >> 3);
                w2a[i] = sb + OFF_W2 + u * 128 + (((cc ^ u) & 7) << 4);
            }
            auto load_piece = [&](int j) {
#pragma unroll
                for (int ks = 0; ks < 3; ks++)
#pragma unroll
                    for (int i = 0; i < 2; i++) ldsm4t(w2f[j][i][ks], w2a[i] + j * W2_BOX + ks * (W2_BOX / 3));
            };
#pragma unroll
            for (int j = 0; j < 2; j++) { mbar_wait(bar_w + 8 * (4 + j), 0); load_piece(j); }
            const bool early = __all_sync(0xffffffffu, mbar_test(bar_w + 8 * 6, 0));
            if (early) load_piece(2);
            uint32_t* c_out = &mail->c[(warp - 3) * 2][fc][g * 4];
            asm volatile("" : "+l"(c_out));
            bar_sync(5, NEPI);
            const uint32_t* ap = (const uint32_t*)(smem + OFF_ACT) + (g & 1) * 24 + t;
            const uint32_t ab[3][2] = {{ap[0], ap[4]}, {ap[8], ap[12]}, {ap[16], ap[20]}};
            float c[4][4];
#pragma unroll
            for (int q = 0; q < 4; q++) { c[q][0] = c[q][1] = c[q][2] = c[q][3] = 0.f; }
#pragma unroll
            for (int ks = 0; ks < 3; ks++)
#pragma unroll
                for (int q = 0; q < 4; q++) mma16(c[q], w2f[q >> 1][q & 1][ks], ab[ks][0], ab[ks][1]);
#pragma unroll
            for (int q = 0; q < 4; q++)
                st_rlx4_if(t == 0, c_out + ((2 - (q >> 1)) * 12 + (q & 1)) * NFFN * 32,
                           tagged(c[q][0], tag), tagged(c[q][1], tag), tagged(c[q][2], tag), tagged(c[q][3], tag));
            if (!early) { mbar_wait(bar_w + 8 * 6, 0); load_piece(2); }
            float d[2][3][4];
#pragma unroll
            for (int ks = 0; ks < 3; ks++)
#pragma unroll
                for (int i = 0; i < 2; i++) {
                    d[i][ks][0] = d[i][ks][1] = d[i][ks][2] = d[i][ks][3] = 0.f;
                    mma16(d[i][ks], w2f[2][i][ks], ab[ks][0], ab[ks][1]);
                }
#pragma unroll
            for (int i = 0; i < 2; i++)
                st_rlx4_if(t == 0, c_out + i * NFFN * 32,
                           tagged((d[i][0][0] + d[i][1][0]) + d[i][2][0], tag), tagged((d[i][0][1] + d[i][1][1]) + d[i][2][1], tag),
                           tagged((d[i][0][2] + d[i][1][2]) + d[i][2][2], tag), tagged((d[i][0][3] + d[i][1][3]) + d[i][2][3], tag));
            __syncwarp();
        }
    }
    if (cta < NRED) {
        float* red3 = (float*)(smem + OFF_RED + 15360);
        if (warp < 8) {
            const uint32_t* cp = &mail->c[cta][tid >> 3][(lane & 7) * 4];
            uint4 v[3];
            uint32_t bad;
            int it = 0;
#pragma unroll 1
            while (__all_sync(0xffffffffu, (ld_rlx(cp - (lane & 7) * 4) ^ tag) & 1)) { if (++it > SPIN_LIMIT) __trap(); }
#pragma unroll 1
            do {
#pragma unroll
                for (int i = 0; i < 3; i++) v[i] = ld_rlx4(cp + i * 1024);
                bad = 0;
#pragma unroll
                for (int i = 0; i < 3; i++) bad = stale4(bad, v[i], tag);
            } while (retry(bad, it));
            float s[4];
            s[0] = (uf(v[0].x) + uf(v[1].x)) + uf(v[2].x);
            s[1] = (uf(v[0].y) + uf(v[1].y)) + uf(v[2].y);
            s[2] = (uf(v[0].z) + uf(v[1].z)) + uf(v[2].z);
            s[3] = (uf(v[0].w) + uf(v[1].w)) + uf(v[2].w);
#pragma unroll
            for (int j = 0; j < 4; j++) s[j] += __shfl_xor_sync(0xffffffffu, s[j], 8);
#pragma unroll
            for (int j = 0; j < 4; j++) s[j] += __shfl_xor_sync(0xffffffffu, s[j], 16);
            if (lane < 8) *(float4*)(red3 + warp * 32 + lane * 4) = make_float4(s[0], s[1], s[2], s[3]);
            __syncwarp();
            bar_arrive(3, NEPI);
        } else {
            __nv_bfloat16* op = out + (t & 1) * DM + cta * 16 + (t >> 1) * 8 + g;
            asm volatile("" : "+l"(op));
            bar_sync(3, NEPI);
            float v[8];
#pragma unroll
            for (int w = 0; w < 8; w++) v[w] = red3[w * 32 + lane];
            const float acc = ((v[0] + v[1]) + (v[2] + v[3])) + ((v[4] + v[5]) + (v[6] + v[7]));
            *op = __float2bfloat16(hres + bfr(acc));
        }
    }
}

typedef CUresult (*EncodeFn)(CUtensorMap*, CUtensorMapDataType, cuuint32_t, void*, const cuuint64_t*, const cuuint64_t*,
                             const cuuint32_t*, const cuuint32_t*, CUtensorMapInterleave, CUtensorMapSwizzle,
                             CUtensorMapL2promotion, CUtensorMapFloatOOBfill);

void make_map_w(EncodeFn enc, CUtensorMap* m, const void* p, uint64_t inner, uint64_t blocks, uint64_t rows,
                uint32_t box_inner, uint32_t box_blocks, uint32_t box_rows, CUtensorMapSwizzle sw) {
    cuuint64_t dims[3] = {inner, blocks, rows};
    cuuint64_t strides[2] = {inner * 2, blocks * inner * 2};
    cuuint32_t box[3] = {box_inner, box_blocks, box_rows};
    cuuint32_t es[3] = {1, 1, 1};
    enc(m, CU_TENSOR_MAP_DATA_TYPE_BFLOAT16, 3, const_cast<void*>(p), dims, strides, box, es, CU_TENSOR_MAP_INTERLEAVE_NONE,
        sw, CU_TENSOR_MAP_L2_PROMOTION_L2_128B, CU_TENSOR_MAP_FLOAT_OOB_FILL_NONE);
}

void make_map_kv(EncodeFn enc, CUtensorMap* m, const void* p) {
    cuuint64_t dims[2] = {64, (cuuint64_t)4 * HKV * SK};
    cuuint64_t strides[1] = {128};
    cuuint32_t box[2] = {64, 128};
    cuuint32_t es[2] = {1, 1};
    enc(m, CU_TENSOR_MAP_DATA_TYPE_BFLOAT16, 2, const_cast<void*>(p), dims, strides, box, es, CU_TENSOR_MAP_INTERLEAVE_NONE,
        CU_TENSOR_MAP_SWIZZLE_128B, CU_TENSOR_MAP_L2_PROMOTION_L2_128B, CU_TENSOR_MAP_FLOAT_OOB_FILL_NONE);
}

}

extern "C" void kernel_launch(void* const* d_in, const int* in_sizes, int n_in, void* d_out, int out_size) {
    static EncodeFn enc = nullptr;
    static void* mail = nullptr;
    if (!enc) {
        cudaGetSymbolAddress(&mail, g_mail);
        void* fn = nullptr;
        cudaDriverEntryPointQueryResult qr;
        cudaGetDriverEntryPoint("cuTensorMapEncodeTiled", &fn, cudaEnableDefault, &qr);
        enc = (EncodeFn)fn;
        cudaFuncSetAttribute(fused_decode_kernel, cudaFuncAttributeMaxDynamicSharedMemorySize, SMEM_BYTES);
    }
    CUtensorMap tk, tv, two, tw1, tw3, tw2;
    make_map_kv(enc, &tk, d_in[1]);
    make_map_kv(enc, &tv, d_in[2]);
    make_map_w(enc, &two, d_in[4], 144, 4, QD, WO_PITCH / 2, 1, 64, CU_TENSOR_MAP_SWIZZLE_NONE);
    make_map_w(enc, &tw1, d_in[6], FF, 1, DM, 48, 1, 192, CU_TENSOR_MAP_SWIZZLE_NONE);
    make_map_w(enc, &tw3, d_in[7], FF, 1, DM, 48, 1, 192, CU_TENSOR_MAP_SWIZZLE_NONE);
    make_map_w(enc, &tw2, d_in[8], 64, 9, FF, 64, 3, 48, CU_TENSOR_MAP_SWIZZLE_128B);
    fused_decode_kernel<<<NCTA, NTHREADS, SMEM_BYTES>>>((const __nv_bfloat16*)d_in[3], (const __nv_bfloat16*)d_in[0], (Mail*)mail,
                                                        (__nv_bfloat16*)d_out, tk, tv, two, tw1, tw3, tw2);
}
```
